```python
import torch

def _softmax(x, axis=-1):
    return torch.softmax(x, dim=axis)
def _gelu(x):
    return torch.nn.functional.gelu(x, approximate="tanh")
def _silu(x):
    return torch.nn.functional.silu(x)
def _sigmoid(x):
    return torch.sigmoid(x)
def _layernorm(x, axis=-1, eps=1e-5):
    m = x.mean(dim=axis, keepdim=True)
    v = x.var(dim=axis, keepdim=True, unbiased=False)
    return (x - m) / torch.sqrt(v + eps)
def _scatter_add(tgt, idx, src, axis=0):
    return tgt.clone().index_add_(axis, idx, src)
def _segment_sum(src, seg, n):
    out = torch.zeros((n,) + src.shape[1:], dtype=src.dtype)
    return out.index_add_(0, seg, src)
def _pad(x, pw):
    flat = tuple(v for pair in reversed(pw) for v in pair)
    return torch.nn.functional.pad(x, flat)

kernel_name = 'recurrent_scan__ssm_conv_s5__glu_gated_geglu__prompt'

def setup_inputs():

    _w = (lambda a: (lambda t: t.to(torch.bfloat16) if t.is_floating_point() else t)(torch.as_tensor(a)))
    def _A_setup():
        B, S, D = 1, 2048, 640
        P = D
        Lambda_re = -0.5 * (lambda _x: torch.exp(torch.as_tensor(_x)))((lambda *s: torch.randn(*s, dtype=torch.bfloat16) * 0.8)(P))
        Lambda_im = (lambda *s: torch.randn(*s, dtype=torch.bfloat16) * 0.8)(P) * 1.0
        B_re = (lambda *s: torch.randn(*s, dtype=torch.bfloat16) * 1.6)(P, D) * (D ** -0.5)
        B_im = (lambda *s: torch.randn(*s, dtype=torch.bfloat16) * 1.6)(P, D) * (D ** -0.5)
        C_re = (lambda *s: torch.randn(*s, dtype=torch.bfloat16) * 1.6)(D, P) * (P ** -0.5)
        C_im = (lambda *s: torch.randn(*s, dtype=torch.bfloat16) * 1.6)(D, P) * (P ** -0.5)
        log_dt = (lambda *s: torch.randn(*s, dtype=torch.bfloat16) * 0.8)(P) * 0.3 - 2.0
        Dskip = (lambda *s: torch.randn(*s, dtype=torch.bfloat16) * 0.8)(D)
        return {
            "x": _w((lambda *s: torch.randn(*s, dtype=torch.bfloat16) * 0.05)(B, S, D)),
            "Lambda_re": _w(Lambda_re),
            "Lambda_im": _w(Lambda_im),
            "B_re": _w(B_re),
            "B_im": _w(B_im),
            "C_re": _w(C_re),
            "C_im": _w(C_im),
            "log_dt": _w(log_dt),
            "Dskip": _w(Dskip),
        }
    _A_in = _A_setup()

    def _B_setup():
        B, S, Dm, Df = 1, 2048, 640, 1728
        return {
            "x": _w((lambda *s: torch.randn(*s, dtype=torch.bfloat16) * 0.05)(B, S, Dm)),
            "w_gate": _w((lambda *s: torch.randn(*s, dtype=torch.bfloat16) * 0.2)(Dm, Df) * (Dm ** -0.5)),
            "w_up": _w((lambda *s: torch.randn(*s, dtype=torch.bfloat16) * 0.2)(Dm, Df) * (Dm ** -0.5)),
            "w_down": _w((lambda *s: torch.randn(*s, dtype=torch.bfloat16) * 0.2)(Df, Dm) * (Df ** -0.5)),
        }
    _B_in = _B_setup()

    return {
        "A_x": _A_in["x"],
        "A_Lambda_re": _A_in["Lambda_re"],
        "A_Lambda_im": _A_in["Lambda_im"],
        "A_B_re": _A_in["B_re"],
        "A_B_im": _A_in["B_im"],
        "A_C_re": _A_in["C_re"],
        "A_C_im": _A_in["C_im"],
        "A_log_dt": _A_in["log_dt"],
        "A_Dskip": _A_in["Dskip"],
        "B_x": _B_in["x"],
        "B_w_gate": _B_in["w_gate"],
        "B_w_up": _B_in["w_up"],
        "B_w_down": _B_in["w_down"],
    }

def reference(A_x, A_Lambda_re, A_Lambda_im, A_B_re, A_B_im, A_C_re, A_C_im, A_log_dt, A_Dskip, B_x, B_w_gate, B_w_up, B_w_down):
    def _A_ref(x, Lambda_re, Lambda_im, B_re, B_im, C_re, C_im, log_dt, Dskip):
        Bsz, L, H = x.shape
        Lam = Lambda_re + 1j * Lambda_im
        Bmat = B_re + 1j * B_im
        Cmat = C_re + 1j * C_im
        dt = torch.exp(log_dt)
        Lam_bar = torch.exp(dt * Lam)
        B_bar = ((Lam_bar - 1.0) / Lam)[:, None] * Bmat
        Bu = torch.einsum("bld,pd->blp", x + 0j, B_bar)
        h = torch.zeros_like(Bu[:, 0, :])
        hs = []
        for t in range(L):
            h = Lam_bar[None, :] * h + Bu[:, t, :]
            hs.append(h)
        hseq = torch.stack(hs, 1)
        y = 2.0 * torch.einsum("blp,dp->bld", hseq, Cmat).real + x * Dskip[None, None, :]
        return y

    def _B_ref(x, w_gate, w_up, w_down):
        g = torch.einsum("bsd,df->bsf", x, w_gate)
        u = torch.einsum("bsd,df->bsf", x, w_up)
        h = _gelu(g) * u
        return torch.einsum("bsf,fd->bsd", h, w_down)

    x = A_x
    xn = _layernorm(x, axis=-1)
    s = _A_ref(xn, A_Lambda_re, A_Lambda_im, A_B_re, A_B_im, A_C_re, A_C_im, A_log_dt, A_Dskip)
    g = _silu(_B_ref(xn, B_w_gate, B_w_up, B_w_down))
    return x + s * g
```

```cpp
#include <cuda_runtime.h>
#include <cuda_bf16.h>
#include <cuda.h>
#include <stdint.h>
#include <stdio.h>

#define CLUSTER 2
#define TIMING 0

namespace {

constexpr int L_ = 2048, D_ = 640, P_ = 640, F_ = 1728;
constexpr int NSPARE = 4;
constexpr int NCTA = 128 + NSPARE;
constexpr int SLOT = 16384;
constexpr int WRING_OFF = 10 * SLOT;
constexpr int BAR_OFF = 14 * SLOT;
constexpr int STAT_OFF = BAR_OFF + 320;
constexpr int CS_OFF = STAT_OFF + 1024;
constexpr int ONES_OFF = CS_OFF + 1024;
constexpr int SMEM_BYTES = ONES_OFF + 128;
constexpr uint32_t SB = 0x400;
constexpr int YN = 216;
constexpr int Y_STAGE = SLOT + YN * 128;
constexpr int Y_STAGES = 5;
constexpr int O_STAGE = 2 * SLOT;
constexpr int O_STAGES = 7;
#define PREFETCH 3
#define NOSTORE 0
#define PACE 0
#define YB 14
#define YU 1
#define NAP 2
#define DRY 0
#define ZINIT 0
#define X_AHEAD 2
#define Y_LEAD 3
#define O_LEAD 4

__device__ __nv_bfloat16 g_H[L_ * F_];
__device__ __nv_bfloat16 g_hT[2 * P_ * L_];
__device__ uint2 g_s[L_ * D_ / 4];
__device__ uint4 g_agg[16 * P_];
__device__ uint2 g_cs[37 * 128];
__device__ uint2 g_stat[L_];
__device__ uint32_t g_ticket;
__device__ uint32_t g_flag[16 * 32];

struct Maps {
  CUtensorMap x, bre, bim, wg, wu, h, wd, ht, cre0, cre1, cim0, cim1, out;
};

__device__ __forceinline__ uint32_t smem_u32(const void* p) { return (uint32_t)__cvta_generic_to_shared(p); }
__device__ __forceinline__ void mbar_init(uint32_t bar, uint32_t count) { asm volatile("mbarrier.init.shared::cta.b64 [%0], %1;" :: "r"(bar), "r"(count) : "memory"); }
__device__ __forceinline__ void mbar_expect_tx(uint32_t bar, uint32_t bytes) { asm volatile("mbarrier.arrive.expect_tx.shared::cta.b64 _, [%0], %1;" :: "r"(bar), "r"(bytes) : "memory"); }
__device__ __forceinline__ void mbar_arrive(uint32_t bar) { asm volatile("mbarrier.arrive.shared::cta.b64 _, [%0];" :: "r"(bar) : "memory"); }
__device__ __forceinline__ void mbar_arrive_cluster(uint32_t bar, uint32_t cta) {
  asm volatile("{\n.reg .b32 ra;\nmapa.shared::cluster.u32 ra, %0, %1;\nmbarrier.arrive.shared::cluster.b64 _, [ra];\n}" :: "r"(bar), "r"(cta) : "memory");
}
__device__ __forceinline__ void mbar_wait(uint32_t bar, uint32_t parity) {
  asm volatile("{\n.reg .pred p;\n.reg .u32 t0, t1;\n"
    "mbarrier.try_wait.parity.shared::cta.b64 p, [%0], %1;\n@p bra LAB_DONE;\n"
    "mov.u32 t0, %%clock;\n"
    "LAB_WAIT:\n"
    "mbarrier.try_wait.parity.shared::cta.b64 p, [%0], %1;\n@p bra LAB_DONE;\n"
    "mov.u32 t1, %%clock;\nsub.u32 t1, t1, t0;\nsetp.gt.u32 p, t1, 1000000000;\n@p trap;\nbra LAB_WAIT;\n"
    "LAB_DONE:\n}" :: "r"(bar), "r"(parity) : "memory");
}
__device__ __forceinline__ void flag_wait_ge(const uint32_t* p, uint32_t target) {
  asm volatile("{\n.reg .pred p;\n.reg .u32 t0, t1;\n.reg .s32 v;\n"
    "mov.u32 t0, %%clock;\n"
    "LAB_WAIT:\n"
    "ld.acquire.gpu.global.u32 v, [%0];\nsub.s32 v, v, %1;\nsetp.ge.s32 p, v, 0;\n@p bra LAB_DONE;\n"
    "mov.u32 t1, %%clock;\nsub.u32 t1, t1, t0;\nsetp.gt.u32 p, t1, 1000000000;\n@p trap;\nbra LAB_WAIT;\n"
    "LAB_DONE:\n}" :: "l"(p), "r"(target) : "memory");
}
__device__ __forceinline__ uint32_t ld_acquire(const uint32_t* p) { uint32_t v; asm volatile("ld.acquire.gpu.global.u32 %0, [%1];" : "=r"(v) : "l"(p) : "memory"); return v; }
__device__ __forceinline__ uint32_t ld_relaxed(const uint32_t* p) { uint32_t v; asm volatile("ld.relaxed.gpu.global.u32 %0, [%1];" : "=r"(v) : "l"(p) : "memory"); return v; }
__device__ __forceinline__ void red_release_add(uint32_t* p, uint32_t v) { asm volatile("red.release.gpu.global.add.u32 [%0], %1;" :: "l"(p), "r"(v) : "memory"); }
__device__ __forceinline__ void st_release(uint32_t* p, uint32_t v) { asm volatile("st.release.gpu.global.u32 [%0], %1;" :: "l"(p), "r"(v) : "memory"); }
__device__ __forceinline__ void fence_proxy_async() { asm volatile("fence.proxy.async.global;" ::: "memory"); }
__device__ __forceinline__ void trap_if(bool c) { asm volatile("{\n.reg .pred p;\nsetp.ne.u32 p, %0, 0;\n@p trap;\n}" :: "r"((uint32_t)c)); }
__device__ __forceinline__ uint32_t clock32() { uint32_t c; asm volatile("mov.u32 %0, %%clock;" : "=r"(c) :: "memory"); return c; }

__device__ __forceinline__ bool elect_one() {
  uint32_t p;
  asm volatile("{\n.reg .pred P;\nelect.sync _|P, 0xffffffff;\nselp.u32 %0, 1, 0, P;\n}" : "=r"(p));
  return p;
}
__device__ __forceinline__ void tma2d(uint32_t dst, const CUtensorMap* map, int c0, int c1, uint32_t bar) {
  asm volatile("cp.async.bulk.tensor.2d.shared::cluster.global.mbarrier::complete_tx::bytes [%0], [%1, {%3, %4}], [%2];"
    :: "r"(dst), "l"(map), "r"(bar), "r"(c0), "r"(c1) : "memory");
}
__device__ __forceinline__ void tma2d_mc(uint32_t dst, const CUtensorMap* map, int c0, int c1, uint32_t bar) {
  asm volatile("cp.async.bulk.tensor.2d.shared::cluster.global.mbarrier::complete_tx::bytes.multicast::cluster [%0], [%1, {%3, %4}], [%2], %5;"
    :: "r"(dst), "l"(map), "r"(bar), "r"(c0), "r"(c1), "h"((uint16_t)3) : "memory");
}
__device__ __forceinline__ void tma3d(uint32_t dst, const CUtensorMap* map, int c0, int c1, int c2, uint32_t bar) {
  asm volatile("cp.async.bulk.tensor.3d.shared::cluster.global.mbarrier::complete_tx::bytes [%0], [%1, {%3, %4, %5}], [%2];"
    :: "r"(dst), "l"(map), "r"(bar), "r"(c0), "r"(c1), "r"(c2) : "memory");
}
__device__ __forceinline__ void tma4d(uint32_t dst, const CUtensorMap* map, int c0, int c1, int c2, int c3, uint32_t bar) {
  asm volatile("cp.async.bulk.tensor.4d.shared::cluster.global.mbarrier::complete_tx::bytes [%0], [%1, {%3, %4, %5, %6}], [%2];"
    :: "r"(dst), "l"(map), "r"(bar), "r"(c0), "r"(c1), "r"(c2), "r"(c3) : "memory");
}
__device__ __forceinline__ void tma5d(uint32_t dst, const CUtensorMap* map, int c0, int c4, uint32_t bar) {
  asm volatile("cp.async.bulk.tensor.5d.shared::cluster.global.mbarrier::complete_tx::bytes [%0], [%1, {%3, %5, %5, %5, %4}], [%2];"
    :: "r"(dst), "l"(map), "r"(bar), "r"(c0), "r"(c4), "r"(0) : "memory");
}
__device__ __forceinline__ void tma5d_mc(uint32_t dst, const CUtensorMap* map, int c0, int c4, uint32_t bar) {
  asm volatile("cp.async.bulk.tensor.5d.shared::cluster.global.mbarrier::complete_tx::bytes.multicast::cluster [%0], [%1, {%3, %5, %5, %5, %4}], [%2], %6;"
    :: "r"(dst), "l"(map), "r"(bar), "r"(c0), "r"(c4), "r"(0), "h"((uint16_t)3) : "memory");
}
__device__ __forceinline__ void bulk_load(uint32_t dst, const void* src, uint32_t bytes, uint32_t bar) {
  asm volatile("cp.async.bulk.shared::cluster.global.mbarrier::complete_tx::bytes [%0], [%1], %2, [%3];" :: "r"(dst), "l"(src), "r"(bytes), "r"(bar) : "memory");
}
__device__ __forceinline__ void tma2d_prefetch(const CUtensorMap* map, int c0, int c1) {
  asm volatile("cp.async.bulk.prefetch.tensor.2d.L2.global [%0, {%1, %2}];" :: "l"(map), "r"(c0), "r"(c1) : "memory");
}
__device__ __forceinline__ void prefetch_l2(const void* p, uint32_t bytes) { asm volatile("cp.async.bulk.prefetch.L2.global [%0], %1;" :: "l"(p), "r"(bytes) : "memory"); }
__device__ __forceinline__ void prefetch_map(const CUtensorMap* map) { asm volatile("prefetch.tensormap [%0];" :: "l"(map) : "memory"); }
__device__ __forceinline__ void wgmma_fence() { asm volatile("wgmma.fence.sync.aligned;" ::: "memory"); }
__device__ __forceinline__ void wgmma_commit() { asm volatile("wgmma.commit_group.sync.aligned;" ::: "memory"); }
template<int N> __device__ __forceinline__ void wgmma_wait() { asm volatile("wgmma.wait_group.sync.aligned %0;" :: "n"(N) : "memory"); }
template<int N> __device__ __forceinline__ void zero_regs(float (&d)[N]) {
#pragma unroll
  for (int i = 0; i < N; i++) asm volatile("mov.b32 %0, 0;" : "=f"(d[i]));
}
template<int N> __device__ __forceinline__ void fence_regs(float (&d)[N]) {
#pragma unroll
  for (int i = 0; i < N; i++) asm volatile("" : "+f"(d[i]) :: "memory");
}
constexpr uint32_t DK = 1u << 16, DMN = 512u << 16;
__device__ __forceinline__ uint64_t mkdesc(uint32_t lo) { return (uint64_t)lo | ((uint64_t)0x40000040u << 32); }
__device__ __forceinline__ bool mbar_try(uint32_t bar, uint32_t parity) {
  uint32_t ok;
  asm volatile("{\n.reg .pred p;\nmbarrier.test_wait.parity.shared::cta.b64 p, [%1], %2;\nselp.u32 %0, 1, 0, p;\n}" : "=r"(ok) : "r"(bar), "r"(parity) : "memory");
  return ok;
}
__device__ __forceinline__ void arrive_if(bool p, uint32_t addr) {
  asm volatile("{\n.reg .pred p;\nsetp.ne.u32 p, %0, 0;\n@p mbarrier.arrive.shared::cluster.b64 _, [%1];\n}" :: "r"((uint32_t)p), "r"(addr) : "memory");
}
__device__ __forceinline__ void peek_clear() { asm volatile("setp.ne.u32 peekp, 0, 0;" ::: "memory"); }
__device__ __forceinline__ void peek(uint32_t bar, uint32_t parity) {
  asm volatile("mbarrier.test_wait.parity.shared::cta.b64 peekp, [%0], %1;" :: "r"(bar), "r"(parity) : "memory");
}
__device__ __forceinline__ void wait_peeked(uint32_t bar, uint32_t parity) {
  asm volatile("{\n.reg .pred p;\n.reg .u32 t0, t1;\n"
    "@peekp bra LAB_DONE;\n"
    "mov.u32 t0, %%clock;\n"
    "LAB_WAIT:\n"
    "mbarrier.try_wait.parity.shared::cta.b64 p, [%0], %1;\n@p bra LAB_DONE;\n"
    "mov.u32 t1, %%clock;\nsub.u32 t1, t1, t0;\nsetp.gt.u32 p, t1, 1000000000;\n@p trap;\nbra LAB_WAIT;\n"
    "LAB_DONE:\n}" :: "r"(bar), "r"(parity) : "memory");
}
__device__ __forceinline__ uint32_t lds_volatile(uint32_t addr) { uint32_t v; asm volatile("ld.acquire.cta.shared::cta.u32 %0, [%1];" : "=r"(v) : "r"(addr) : "memory"); return v; }
__device__ __forceinline__ void sts_release(uint32_t addr, uint32_t v) { asm volatile("st.release.cta.shared::cta.u32 [%0], %1;" :: "r"(addr), "r"(v) : "memory"); }
__device__ __forceinline__ uint32_t smem_wait_bits(uint32_t addr, uint32_t mask) {
  uint32_t v;
  asm volatile("{\n.reg .pred p;\n.reg .u32 t0, t1;\n"
    "mov.u32 t0, %%clock;\n"
    "LAB_WAIT:\n"
    "ld.acquire.cta.shared::cta.u32 %0, [%1];\nand.b32 t1, %0, %2;\nsetp.ne.u32 p, t1, 0;\n@p bra LAB_DONE;\n"
    "mov.u32 t1, %%clock;\nsub.u32 t1, t1, t0;\nsetp.gt.u32 p, t1, 1000000000;\n@p trap;\nbra LAB_WAIT;\n"
    "LAB_DONE:\n}" : "=r"(v) : "r"(addr), "r"(mask) : "memory");
  return v;
}
__device__ __forceinline__ void ldsm4(uint32_t& r0, uint32_t& r1, uint32_t& r2, uint32_t& r3, uint32_t addr) {
  asm volatile("ldmatrix.sync.aligned.m8n8.x4.shared.b16 {%0,%1,%2,%3}, [%4];" : "=r"(r0), "=r"(r1), "=r"(r2), "=r"(r3) : "r"(addr) : "memory");
}
__device__ __forceinline__ void ldsm2(uint32_t& r0, uint32_t& r1, uint32_t addr) {
  asm volatile("ldmatrix.sync.aligned.m8n8.x2.shared.b16 {%0,%1}, [%2];" : "=r"(r0), "=r"(r1) : "r"(addr) : "memory");
}
__device__ __forceinline__ uint4 ld_relaxed128(const void* p) {
  uint64_t a, b;
  asm volatile("ld.relaxed.gpu.global.v2.u64 {%0, %1}, [%2];" : "=l"(a), "=l"(b) : "l"(p) : "memory");
  return make_uint4((uint32_t)a, (uint32_t)(a >> 32), (uint32_t)b, (uint32_t)(b >> 32));
}
__device__ __forceinline__ void st_tagged(void* p, float v, uint32_t tag) {
  asm volatile("st.relaxed.gpu.global.u64 [%0], %1;" :: "l"(p), "l"((uint64_t)__float_as_uint(v) | ((uint64_t)tag << 32)) : "memory");
}
__device__ __forceinline__ void cluster_sync_relaxed() {
  asm volatile("barrier.cluster.arrive.relaxed.aligned;\nbarrier.cluster.wait.aligned;" ::: "memory");
}
__device__ __forceinline__ void bar_sync(int id, int n) { asm volatile("bar.sync %0, %1;" :: "r"(id), "r"(n) : "memory"); }
__device__ __forceinline__ void bar_arrive(int id, int n) { asm volatile("bar.arrive %0, %1;" :: "r"(id), "r"(n) : "memory"); }
__device__ __forceinline__ void bar_arrive_if(bool p, int id) {
  asm volatile("{\n.reg .pred p;\nsetp.ne.u32 p, %0, 0;\n@p bar.arrive %1, 256;\n}" :: "r"((uint32_t)p), "r"(id) : "memory");
}
template<int R> __device__ __forceinline__ void reg_alloc() { asm volatile("setmaxnreg.inc.sync.aligned.u32 %0;" :: "n"(R)); }
template<int R> __device__ __forceinline__ void reg_dealloc() { asm volatile("setmaxnreg.dec.sync.aligned.u32 %0;" :: "n"(R)); }
__device__ __forceinline__ uint32_t pack_bf16(float lo, float hi) { uint32_t r; asm("cvt.rn.bf16x2.f32 %0, %1, %2;" : "=r"(r) : "f"(hi), "f"(lo)); return r; }
__device__ __forceinline__ float bf_lo(uint32_t v) { return __uint_as_float(v << 16); }
__device__ __forceinline__ float bf_hi(uint32_t v) { return __uint_as_float(v & 0xffff0000u); }
__device__ __forceinline__ float round_bf(float v) { return bf_lo(pack_bf16(v, 0.f)); }
__device__ __forceinline__ float ex2(float x) { float y; asm("ex2.approx.ftz.f32 %0, %1;" : "=f"(y) : "f"(x)); return y; }
__device__ __forceinline__ float rcp(float x) { float y; asm("rcp.approx.ftz.f32 %0, %1;" : "=f"(y) : "f"(x)); return y; }
__device__ __forceinline__ uint32_t ldg32(const void* p) { uint32_t v; asm volatile("ld.global.u32 %0, [%1];" : "=r"(v) : "l"(p) : "memory"); return v; }
__device__ __forceinline__ uint32_t hmul2_bf(uint32_t a, uint32_t b) { uint32_t r; asm("mul.rn.bf16x2 %0, %1, %2;" : "=r"(r) : "r"(a), "r"(b)); return r; }
__device__ __forceinline__ uint32_t hadd2_bf(uint32_t a, uint32_t b) { uint32_t r; asm("add.rn.bf16x2 %0, %1, %2;" : "=r"(r) : "r"(a), "r"(b)); return r; }
__device__ __forceinline__ uint32_t hfma2_bf(uint32_t a, uint32_t b, uint32_t c) { uint32_t r; asm("fma.rn.bf16x2 %0, %1, %2, %3;" : "=r"(r) : "r"(a), "r"(b), "r"(c)); return r; }
__device__ __forceinline__ void stg128(void* p, uint32_t a, uint32_t b, uint32_t c, uint32_t d) { asm volatile("st.global.v4.u32 [%0], {%1,%2,%3,%4};" :: "l"(p), "r"(a), "r"(b), "r"(c), "r"(d) : "memory"); }

template<int N, int TA, int TB> struct WgmmaSS;
template<int TA, int TB> struct WgmmaSS<8, TA, TB> {
  static __device__ __forceinline__ void mma(float (&d)[4], uint64_t da, uint64_t db, int scale_d) {
    asm volatile("{\n.reg .pred p;\nsetp.ne.b32 p, %6, 0;\n"
      "wgmma.mma_async.sync.aligned.m64n8k16.f32.bf16.bf16 {"
      "%0, %1, %2, %3"
      "}, %4, %5, p, 1, 1, %7, %8;\n}\n"
      :
        "+f"(d[0]), "+f"(d[1]), "+f"(d[2]), "+f"(d[3])
      : "l"(da), "l"(db), "r"(scale_d), "n"(TA), "n"(TB));
  }
};
template<int TA, int TB> struct WgmmaSS<128, TA, TB> {
  static __device__ __forceinline__ void mma(float (&d)[64], uint64_t da, uint64_t db, int scale_d) {
    asm volatile("{\n.reg .pred p;\nsetp.ne.b32 p, %66, 0;\n"
      "wgmma.mma_async.sync.aligned.m64n128k16.f32.bf16.bf16 {"
      "%0, %1, %2, %3, %4, %5, %6, %7, %8, %9, %10, %11, %12, %13, %14, %15, "
      "%16, %17, %18, %19, %20, %21, %22, %23, %24, %25, %26, %27, %28, %29, %30, %31, "
      "%32, %33, %34, %35, %36, %37, %38, %39, %40, %41, %42, %43, %44, %45, %46, %47, "
      "%48, %49, %50, %51, %52, %53, %54, %55, %56, %57, %58, %59, %60, %61, %62, %63"
      "}, %64, %65, p, 1, 1, %67, %68;\n}\n"
      :
        "+f"(d[0]), "+f"(d[1]), "+f"(d[2]), "+f"(d[3]), "+f"(d[4]), "+f"(d[5]), "+f"(d[6]), "+f"(d[7]),
        "+f"(d[8]), "+f"(d[9]), "+f"(d[10]), "+f"(d[11]), "+f"(d[12]), "+f"(d[13]), "+f"(d[14]), "+f"(d[15]),
        "+f"(d[16]), "+f"(d[17]), "+f"(d[18]), "+f"(d[19]), "+f"(d[20]), "+f"(d[21]), "+f"(d[22]), "+f"(d[23]),
        "+f"(d[24]), "+f"(d[25]), "+f"(d[26]), "+f"(d[27]), "+f"(d[28]), "+f"(d[29]), "+f"(d[30]), "+f"(d[31]),
        "+f"(d[32]), "+f"(d[33]), "+f"(d[34]), "+f"(d[35]), "+f"(d[36]), "+f"(d[37]), "+f"(d[38]), "+f"(d[39]),
        "+f"(d[40]), "+f"(d[41]), "+f"(d[42]), "+f"(d[43]), "+f"(d[44]), "+f"(d[45]), "+f"(d[46]), "+f"(d[47]),
        "+f"(d[48]), "+f"(d[49]), "+f"(d[50]), "+f"(d[51]), "+f"(d[52]), "+f"(d[53]), "+f"(d[54]), "+f"(d[55]),
        "+f"(d[56]), "+f"(d[57]), "+f"(d[58]), "+f"(d[59]), "+f"(d[60]), "+f"(d[61]), "+f"(d[62]), "+f"(d[63])
      : "l"(da), "l"(db), "r"(scale_d), "n"(TA), "n"(TB));
  }
};
template<int TA, int TB> struct WgmmaSS<216, TA, TB> {
  static __device__ __forceinline__ void mma(float (&d)[108], uint64_t da, uint64_t db, int scale_d) {
    asm volatile("{\n.reg .pred p;\nsetp.ne.b32 p, %110, 0;\n"
      "wgmma.mma_async.sync.aligned.m64n216k16.f32.bf16.bf16 {"
      "%0, %1, %2, %3, %4, %5, %6, %7, %8, %9, %10, %11, %12, %13, %14, %15, "
      "%16, %17, %18, %19, %20, %21, %22, %23, %24, %25, %26, %27, %28, %29, %30, %31, "
      "%32, %33, %34, %35, %36, %37, %38, %39, %40, %41, %42, %43, %44, %45, %46, %47, "
      "%48, %49, %50, %51, %52, %53, %54, %55, %56, %57, %58, %59, %60, %61, %62, %63, "
      "%64, %65, %66, %67, %68, %69, %70, %71, %72, %73, %74, %75, %76, %77, %78, %79, "
      "%80, %81, %82, %83, %84, %85, %86, %87, %88, %89, %90, %91, %92, %93, %94, %95, "
      "%96, %97, %98, %99, %100, %101, %102, %103, %104, %105, %106, %107"
      "}, %108, %109, p, 1, 1, %111, %112;\n}\n"
      :
        "+f"(d[0]), "+f"(d[1]), "+f"(d[2]), "+f"(d[3]), "+f"(d[4]), "+f"(d[5]), "+f"(d[6]), "+f"(d[7]),
        "+f"(d[8]), "+f"(d[9]), "+f"(d[10]), "+f"(d[11]), "+f"(d[12]), "+f"(d[13]), "+f"(d[14]), "+f"(d[15]),
        "+f"(d[16]), "+f"(d[17]), "+f"(d[18]), "+f"(d[19]), "+f"(d[20]), "+f"(d[21]), "+f"(d[22]), "+f"(d[23]),
        "+f"(d[24]), "+f"(d[25]), "+f"(d[26]), "+f"(d[27]), "+f"(d[28]), "+f"(d[29]), "+f"(d[30]), "+f"(d[31]),
        "+f"(d[32]), "+f"(d[33]), "+f"(d[34]), "+f"(d[35]), "+f"(d[36]), "+f"(d[37]), "+f"(d[38]), "+f"(d[39]),
        "+f"(d[40]), "+f"(d[41]), "+f"(d[42]), "+f"(d[43]), "+f"(d[44]), "+f"(d[45]), "+f"(d[46]), "+f"(d[47]),
        "+f"(d[48]), "+f"(d[49]), "+f"(d[50]), "+f"(d[51]), "+f"(d[52]), "+f"(d[53]), "+f"(d[54]), "+f"(d[55]),
        "+f"(d[56]), "+f"(d[57]), "+f"(d[58]), "+f"(d[59]), "+f"(d[60]), "+f"(d[61]), "+f"(d[62]), "+f"(d[63]),
        "+f"(d[64]), "+f"(d[65]), "+f"(d[66]), "+f"(d[67]), "+f"(d[68]), "+f"(d[69]), "+f"(d[70]), "+f"(d[71]),
        "+f"(d[72]), "+f"(d[73]), "+f"(d[74]), "+f"(d[75]), "+f"(d[76]), "+f"(d[77]), "+f"(d[78]), "+f"(d[79]),
        "+f"(d[80]), "+f"(d[81]), "+f"(d[82]), "+f"(d[83]), "+f"(d[84]), "+f"(d[85]), "+f"(d[86]), "+f"(d[87]),
        "+f"(d[88]), "+f"(d[89]), "+f"(d[90]), "+f"(d[91]), "+f"(d[92]), "+f"(d[93]), "+f"(d[94]), "+f"(d[95]),
        "+f"(d[96]), "+f"(d[97]), "+f"(d[98]), "+f"(d[99]), "+f"(d[100]), "+f"(d[101]), "+f"(d[102]), "+f"(d[103]),
        "+f"(d[104]), "+f"(d[105]), "+f"(d[106]), "+f"(d[107])
      : "l"(da), "l"(db), "r"(scale_d), "n"(TA), "n"(TB));
  }
};

#define TWAIT(stmt) stmt
#define TSTAMP_L0(slot) do {} while (0)
#define TDECL
#define TRACE(i)
#define TRACE1(i)
#define TDUMP(slot)
#define TVAL(slot, v) do {} while (0)
#define TSTAMP(slot) do {} while (0)
#define TSTAMP_WG(slot) do {} while (0)

template<bool B> struct BoolTag { static constexpr bool value = B; };
struct cplx { float r, i; };
__device__ __forceinline__ cplx cmul(cplx a, cplx b) { return {fmaf(a.r, b.r, -a.i * b.i), fmaf(a.r, b.i, a.i * b.r)}; }
__device__ __forceinline__ cplx cmulc(cplx a, cplx b) { return {fmaf(a.r, b.r, -a.i * b.i), fmaf(-a.r, b.i, -a.i * b.r)}; }
__device__ __forceinline__ cplx cfma(cplx a, cplx b, cplx c) { return {fmaf(a.r, b.r, fmaf(-a.i, b.i, c.r)), fmaf(a.r, b.i, fmaf(a.i, b.r, c.i))}; }
__device__ __forceinline__ cplx csel(bool p, cplx a, cplx b) { return {p ? a.r : b.r, p ? a.i : b.i}; }
__device__ __forceinline__ cplx cshfl(cplx a, int src) { return {__shfl_sync(0xffffffffu, a.r, src), __shfl_sync(0xffffffffu, a.i, src)}; }

__device__ __forceinline__ void yield_slot(int nap, int zero, uint32_t prev, float& root) {
  asm volatile("{\n.reg .pred p;\nsetp.eq.s32 p, %3, 0;\n@p bra.uni LAB_SKIP;\nnanosleep.u32 0;\nlop3.b32 %0, %0, %1, %2, 0x78;\nLAB_SKIP:\n}"
    : "+f"(root) : "r"(prev), "r"(zero), "r"(nap));
}
__device__ __forceinline__ void yield_slot(int nap, int zero, uint32_t prev, float& root0, float& root1) {
  asm volatile("{\n.reg .pred p;\nsetp.eq.s32 p, %4, 0;\n@p bra.uni LAB_SKIP;\nnanosleep.u32 0;\nlop3.b32 %0, %0, %2, %3, 0x78;\nlop3.b32 %1, %1, %2, %3, 0x78;\nLAB_SKIP:\n}"
    : "+f"(root0), "+f"(root1) : "r"(prev), "r"(zero), "r"(nap));
}
__device__ __forceinline__ float tanh_fast(float x) { float y; asm("tanh.approx.f32 %0, %1;" : "=f"(y) : "f"(x)); return y; }
__device__ __forceinline__ void ssm_params(float ar, float ai, float ldt, cplx& lam, cplx& coef2) {
  const float L2E = 1.4426950408889634f;
  const float dt = round_bf(ex2(ldt * L2E));
  const float xr = dt * ar, th = dt * ai;
  const float hi = xr * L2E, lo = fmaf(xr, L2E, -hi) + xr * 1.925963033500011e-8f;
  const float e = ex2(hi) * fmaf(lo, 0.6931471805599453f, 1.0f);
  const float kf = rintf(th * 0.6366197723675814f);
  float r = fmaf(kf, -1.5707963705062866f, th);
  r = fmaf(kf, 4.371138828673793e-8f, r);
  r = fmaf(kf, 1.7151245100058819e-15f, r);
  const int k = (int)kf;
  const float r2 = r * r;
  float sp = fmaf(r2, -1.9515295891e-4f, 8.3321608736e-3f); sp = fmaf(sp, r2, -1.6666654611e-1f); sp = fmaf(sp * r2, r, r);
  float cp = fmaf(r2, 2.443315711809948e-5f, -1.388731625493765e-3f); cp = fmaf(cp, r2, 4.166664568298827e-2f); cp = fmaf(cp, r2, -0.5f); cp = fmaf(cp, r2, 1.0f);
  float sn = (k & 1) ? cp : sp, cs = (k & 1) ? sp : cp;
  sn = (k & 2) ? -sn : sn; cs = ((k + 1) & 2) ? -cs : cs;
  lam.r = e * cs; lam.i = e * sn;
  const bool sw = fabsf(ar) < fabsf(ai);
  const float p = sw ? ai : ar, qq = sw ? ar : ai;
  const float nr = lam.r - 1.0f, ni = lam.i;
  const float t = __fdividef(qq, p), id = __fdividef(2.0f, fmaf(qq, t, p));
  coef2.r = (sw ? fmaf(nr, t, ni) : fmaf(ni, t, nr)) * id;
  coef2.i = (sw ? fmaf(ni, t, -nr) : fmaf(-nr, t, ni)) * id;
}

constexpr uint32_t XFULL = 0, WFULL = 80, WEMPTY = 112, PFULL = 144, PEMPTY = 200, EPOCH = 256, READY = 260;
constexpr int NB_ORDER = 2  , NB_FLAG = 4  , NB_CS = 6  , NB_LEAD = 8;

struct Ptrs { const __nv_bfloat16 *x, *lam_re, *lam_im, *log_dt, *dskip, *bre, *bim, *cre, *cim, *wd; int zero; };

__device__ __forceinline__ int job_block(int j, int role) {
  return role + (j == 0 ? 0 : j == 1 ? 10 : j == 2 ? (role < 2 ? 8 : 16) : j == 3 ? 24 : 29);
}

__device__ __forceinline__ int sum_block(int u) { return u < 8 ? u + 10 : u < 18 ? u - 8 : u; }

__global__ void __launch_bounds__(384, 1) fused_kernel(const __grid_constant__ Maps maps, const Ptrs ptrs) {
  extern __shared__ __align__(1024) uint8_t smem_raw[];
  asm volatile(".reg .pred peekp;");
  const int warp = __shfl_sync(0xffffffffu, threadIdx.x >> 5, 0);
  const int lane = threadIdx.x & 31;
  const bool spare = blockIdx.x < NSPARE;
  const int cta = (int)blockIdx.x - NSPARE;
  const int m = cta & 15;
  const int role = cta >> 4;
  const int rank = blockIdx.x & 1;
  const bool is_y = role < 3;
  const int njobs = is_y ? 4 : 5;

  uint32_t sb = smem_u32(smem_raw);
  asm volatile("mov.u32 %0, %0;" : "+r"(sb));
  const uint32_t bars = sb + BAR_OFF;

  if (warp == 8) {
    if (elect_one()) {
      TSTAMP(0);
      TRACE1(127);
#pragma unroll
      for (int i = 0; i < 14; i++) mbar_init(bars + i * 8, 1);
      asm volatile("fence.mbarrier_init.release.cluster;" ::: "memory");
      if (!spare) {
        mbar_expect_tx(bars + XFULL, SLOT);
        tma4d(sb, &maps.x, 0, 0, m * 4, 0, bars + XFULL);
        mbar_expect_tx(bars + WFULL, SLOT);
        tma2d(sb + WRING_OFF, &maps.wg, role * 64, 0, bars + WFULL);
        tma2d(sb + WRING_OFF + 8192, &maps.wu, role * 64, 0, bars + WFULL);
        mbar_expect_tx(bars + WFULL + 8, SLOT);
        tma2d(sb + WRING_OFF + SLOT, &maps.bre, 0, role * 64, bars + WFULL + 8);
        tma2d(sb + WRING_OFF + SLOT + 8192, &maps.bim, 0, role * 64, bars + WFULL + 8);
      }
      TSTAMP(50);
    }
    __syncwarp();
  } else if (warp == 9) {
    trap_if((sb & 0xffffffu) != SB);
    if (elect_one()) {
#pragma unroll
      for (int i = 14; i < 32; i++) mbar_init(bars + i * 8, i < 18 ? CLUSTER : i < 25 ? 1 : 2 * CLUSTER);
      asm volatile("st.shared.v2.u32 [%0], {0, 0};" :: "r"(bars + EPOCH) : "memory");
      asm volatile("fence.mbarrier_init.release.cluster;" ::: "memory");
    }
    __syncwarp();
  } else if (warp == 10) {
    asm volatile("st.shared.u32 [%0], %1;" :: "r"(sb + ONES_OFF + lane * 4), "r"(0x3f803f80u) : "memory");
    asm volatile("fence.proxy.async.shared::cta;" ::: "memory");
  }
  __syncthreads();
  cluster_sync_relaxed();
  if (threadIdx.x == 0) TSTAMP(54);

  if (warp >= 8) {
    reg_dealloc<40>();
    if (spare) {
      if (warp == 8) {
        int s = 0; uint32_t ph = 1;
#pragma unroll 1
        for (int u = blockIdx.x; u < 37; u += NSPARE) {
          const int b = sum_block(u);
          const bool isB = b < 10;
          const int blk = (isB ? b : b - 10) * 64;
#pragma unroll 1
          for (int kb = 0; kb < 5; kb++) {
            mbar_wait(bars + PEMPTY + s * 8, ph);
            if (elect_one()) {
              mbar_expect_tx(bars + PFULL + s * 8, O_STAGE);
#pragma unroll 1
              for (int i = 0; i < 4; i++) {
                const int k0 = kb * 128 + (i & 1) * 64;
                tma2d(sb + s * O_STAGE + i * 8192, i & 2 ? (isB ? &maps.bim : &maps.wu) : (isB ? &maps.bre : &maps.wg), isB ? k0 : blk, isB ? blk : k0, bars + PFULL + s * 8);
              }
            }
            __syncwarp();
            if (++s == O_STAGES) { s = 0; ph ^= 1; }
          }
        }
#pragma unroll 1
        for (int i = blockIdx.x; i < 64; i += NSPARE) {
          if (elect_one()) {
            prefetch_l2(ptrs.cre + (size_t)i * (P_ * D_ / 64), P_ * D_ * 2 / 64);
            prefetch_l2(ptrs.cim + (size_t)i * (P_ * D_ / 64), P_ * D_ * 2 / 64);
            prefetch_l2(ptrs.wd + (size_t)i * (F_ * D_ / 64), F_ * D_ * 2 / 64);
          }
          __syncwarp();
        }
      } else if (warp == 11 && lane == 0) {
        uint32_t ep;
        asm volatile("atom.relaxed.gpu.global.add.u32 %0, [%1], 1;" : "=r"(ep) : "l"(&g_ticket) : "memory");
        sts_release(bars + EPOCH, ep / NCTA + 1u);
      }
      __syncwarp();
    } else if (warp == 8) {
      int j = 1, kb = 1;
#pragma unroll 1
      for (int it = 2; it < njobs * 10; it++) {
        const int b = job_block(j, role);
        const bool isB = b < 10;
        const int blk = (isB ? b : b - 10) * 64;
        const int s = it & 3;
        mbar_wait(bars + WEMPTY + s * 8, ((it >> 2) & 1) ^ 1);
        if (elect_one()) {
          if (it == 2) {
            mbar_expect_tx(bars + XFULL + 8, SLOT);
            tma4d(sb + SLOT, &maps.x, 64, 0, m * 4, 0, bars + XFULL + 8);
          }
          const uint32_t dst = sb + WRING_OFF + s * SLOT, fb = bars + WFULL + s * 8;
          const int c0 = isB ? kb * 64 : blk, c1 = isB ? blk : kb * 64;
          mbar_expect_tx(fb, SLOT);
          tma2d_mc(dst + rank * 8192, isB ? (rank ? &maps.bim : &maps.bre) : (rank ? &maps.wu : &maps.wg), c0, c1, fb);
          if (j == 0 && kb + X_AHEAD < 10) {
#pragma unroll 1
            for (int k = kb == 1 ? 2 : kb + X_AHEAD; k <= kb + X_AHEAD; k++) {
              mbar_expect_tx(bars + XFULL + k * 8, SLOT);
              tma4d(sb + k * SLOT, &maps.x, k * 64, 0, m * 4, 0, bars + XFULL + k * 8);
            }
          }
          if (it == 3) {
            if (m < 8) { tma2d_prefetch(&maps.wg, role * 64, (m + 2) * 64); tma2d_prefetch(&maps.wu, role * 64, (m + 2) * 64); }
            else { tma2d_prefetch(&maps.bre, (m - 6) * 64, role * 64); tma2d_prefetch(&maps.bim, (m - 6) * 64, role * 64); }
          }
        }
        __syncwarp();
        if (it < 19) { j ^= 1; kb += j; }
        else if (++kb == 10) { kb = 0; j += j ? 1 : 2; }
      }
      if (is_y) {
        const int d0 = role == 2 ? D_ - YN : role * YN;
        smem_wait_bits(bars + READY, 1u << 27);
        fence_proxy_async();
        int s = 0; uint32_t ph = 0;
#pragma unroll 1
        for (int kk = 0; kk < 20; kk++) {
          mbar_wait(bars + PEMPTY + s * 8, ph);
          if (kk == 16) { smem_wait_bits(bars + READY, 1u << 30); fence_proxy_async(); }
          if (elect_one()) {
            const uint32_t dst = sb + s * Y_STAGE, fb = bars + PFULL + s * 8;
            const bool im = kk & 1;
            const int kc = (kk >> 1) * 64;
            mbar_expect_tx(fb, Y_STAGE);
            TRACE1(kk * 4 + 2);
            tma3d(dst, &maps.ht, 0, kc + (im ? P_ : 0), m * 2, fb);
            const CUtensorMap* mc = rank ? (im ? &maps.cim1 : &maps.cre1) : (im ? &maps.cim0 : &maps.cre0);
            tma2d_mc(dst + SLOT + rank * 112 * 128, mc, kc, d0 + rank * 112, fb);
          }
          __syncwarp();
          if (++s == Y_STAGES) { s = 0; ph ^= 1; }
        }
      } else {
        const int n0 = (role - 3) * 128;
        uint32_t ready = 0;
        int s = 0; uint32_t ph = 0;
#pragma unroll 1
        for (int kk = 0; kk < 29; kk++) {
          mbar_wait(bars + PEMPTY + s * 8, ph);
          const uint32_t bit = 1u << (kk < 27 ? kk : kk + 1);
          if (!(ready & bit)) {
            ready = smem_wait_bits(bars + READY, bit);
            fence_proxy_async();
          }
          if (elect_one()) {
            const uint32_t dst = sb + s * O_STAGE, fb = bars + PFULL + s * 8;
            TRACE1(kk * 4 + 2);
            if (kk < 27) {
              mbar_expect_tx(fb, O_STAGE);
              tma2d(dst, &maps.h, kk * 64, m * 128, fb);
              tma5d_mc(dst + SLOT + rank * 8192, &maps.wd, n0 + rank * 64, kk * 2, fb);
            } else {
              mbar_expect_tx(fb, 4 * 4096);
              for (int i = 0; i < 4; i++) {
                const uint2* src = g_s + ((size_t)(m * 8 + (kk - 27) * 4 + i) * 80 + (role - 3) * 16) * 32;
                asm volatile("cp.async.bulk.shared::cluster.global.mbarrier::complete_tx::bytes [%0], [%1], %2, [%3];"
                  :: "r"(dst + i * 8192), "l"(src), "r"(4096), "r"(fb) : "memory");
              }
            }
          }
          __syncwarp();
          if (++s == O_STAGES) { s = 0; ph ^= 1; }
        }
      }
    } else {
      uint32_t ep = 0;
      if (warp == 11 && lane == 0) {
        asm volatile("atom.relaxed.gpu.global.add.u32 %0, [%1], 1;" : "=r"(ep) : "l"(&g_ticket) : "memory");
        if (is_y) { prefetch_map(&maps.ht); prefetch_map(&maps.cre0); prefetch_map(&maps.cre1); prefetch_map(&maps.cim0); prefetch_map(&maps.cim1); }
        else { prefetch_map(&maps.h); prefetch_map(&maps.wd); prefetch_map(&maps.out); }
        sts_release(bars + EPOCH, ep / NCTA + 1u);
      }
      __syncwarp();
      ep = smem_wait_bits(bars + EPOCH, 0xffffffffu);
      if (warp < 11) {
        const int wg = warp - 9;
        {
          const int rho = role * 16 + wg * 8 + (lane >> 2);
          const uint4* row = reinterpret_cast<const uint4*>(smem_raw + rho * 128) + ((lane & 3) ^ ((lane & 4)));
          float s0 = 0.f, s1 = 0.f, q0 = 0.f, q1 = 0.f;
#pragma unroll 1
          for (int kb = 0; kb < 10; kb++, row += SLOT / 16) {
            mbar_wait(bars + XFULL + kb * 8, 0);
            const uint4 v = row[0], u = row[(lane & 4) ? -4 : 4];
            const uint32_t w[8] = {v.x, v.y, v.z, v.w, u.x, u.y, u.z, u.w};
#pragma unroll
            for (int k = 0; k < 8; k++) { const float a = bf_lo(w[k]), c = bf_hi(w[k]); s0 += a; s1 += c; q0 = fmaf(a, a, q0); q1 = fmaf(c, c, q1); }
          }
          s0 += s1; q0 += q1;
#pragma unroll
          for (int o = 1; o < 4; o <<= 1) { s0 += __shfl_xor_sync(0xffffffffu, s0, o); q0 += __shfl_xor_sync(0xffffffffu, q0, o); }
          const float mean = s0 * (1.0f / D_);
          float den;
          asm("sqrt.approx.f32 %0, %1;" : "=f"(den) : "f"(round_bf(round_bf(fmaxf(fmaf(-mean, mean, q0 * (1.0f / D_)), 0.f)) + 1e-5f)));
          if ((lane & 3) == 0) st_tagged(&g_stat[m * 128 + rho], __uint_as_float(pack_bf16(mean, den)), ep);
          __syncwarp();
          if (wg == 0) TSTAMP_L0(1);
        }
        int j = wg;
#pragma unroll 1
        while (j < njobs) {
          const int b = job_block(j, role);
          const uint2* src = g_cs + b * 128 + lane * 4;
          const uint2* src2 = j < 2 ? g_stat + m * 128 + lane * 4 : src;
          uint4 v0, v1, v2, v3;
          const uint32_t t0 = clock32();
          bool ok;
          do {
            v0 = ld_relaxed128(src); v1 = ld_relaxed128(src + 2); v2 = ld_relaxed128(src2); v3 = ld_relaxed128(src2 + 2);
            ok = (v0.y == ep && v0.w == ep && v1.y == ep && v1.w == ep && v2.y == ep && v2.w == ep && v3.y == ep && v3.w == ep) || clock32() - t0 > 1000000000u;
          } while (!__all_sync(0xffffffffu, ok));
          if (j < 2) {
            float4* dst = reinterpret_cast<float4*>(smem_raw + STAT_OFF) + lane * 2;
            dst[0] = make_float4(-bf_lo(v2.x), rcp(bf_hi(v2.x)), -bf_lo(v2.z), rcp(bf_hi(v2.z)));
            dst[1] = make_float4(-bf_lo(v3.x), rcp(bf_hi(v3.x)), -bf_lo(v3.z), rcp(bf_hi(v3.z)));
          }
          reinterpret_cast<uint4*>(smem_raw + CS_OFF + wg * 512)[lane] = make_uint4(v0.x, v0.z, v1.x, v1.z);
          TSTAMP_L0(57 + j);
          bar_arrive(NB_CS + wg, 160);
          bar_sync(NB_FLAG + wg, 160);
          fence_proxy_async();
          if (lane == 0) {
            if (b < 10) red_release_add(&g_flag[m * 32 + (b < 8 ? 27 : 30)], 1u);
            else st_release(&g_flag[m * 32 + b - 10], ep);
          }
          __syncwarp();
          j = wg ? j * 2 : j + 3;
        }
        if (is_y) {
          bar_sync(NB_FLAG + wg, 160);
          fence_proxy_async();
          if (lane == 0) red_release_add(&g_flag[m * 32 + 28 + wg], 1u);
          TSTAMP_L0(4 + wg);
          __syncwarp();
        }
      } else {
        const uint32_t target = ep * (lane < 27 ? 1u : lane == 27 ? 8u : lane == 30 ? 2u : 3u);
        const uint32_t need = is_y ? 0x48000000u : 0x37ffffffu;
        uint32_t ready = 0;
        const uint32_t t0 = clock32();
        while (ready != need && clock32() - t0 < 1000000000u) {
          const uint32_t now = __ballot_sync(0xffffffffu, ld_relaxed(&g_flag[m * 32 + lane]) == target) & need;
          if (now != ready) {
            ready = now;
            asm volatile("fence.acquire.gpu;" ::: "memory");
            fence_proxy_async();
            if (lane == 0) sts_release(bars + READY, ready);
          }
          if (!(ready >> 26 & 1)) __nanosleep(300);
        }
      }
    }
    cluster_sync_relaxed();
  } else {
    reg_alloc<232>();
    const int wg = warp >> 2;
    const int w4 = warp & 3;
    const int q = lane & 3, r8 = lane >> 2;
    const float2* s_stat = reinterpret_cast<const float2*>(smem_raw + STAT_OFF);
    float* s_cs = reinterpret_cast<float*>(smem_raw + CS_OFF + wg * 512);

    if (spare) {
      const uint32_t ep = smem_wait_bits(bars + EPOCH, 0xffffffffu);
      int s = 0; uint32_t ph = 0;
#pragma unroll 1
      for (int u = blockIdx.x; u < 37; u += NSPARE) {
        const int b = sum_block(u);
        float cs[4];
        zero_regs(cs);
#pragma unroll 1
        for (int kb = 0; kb < 5; kb++) {
          mbar_wait(bars + PFULL + s * 8, ph);
          const uint32_t ad = (SB >> 4) + s * (O_STAGE >> 4) + wg * 1024;
          if (b < 10) {
            wgmma_fence();
#pragma unroll
            for (int k = 0; k < 8; k++) WgmmaSS<8, 0, 0>::mma(cs, mkdesc(ad + DK + (k >> 2) * 512 + (k & 3) * 2), (uint64_t)((SB + ONES_OFF) >> 4), 1);
            wgmma_commit();
            wgmma_wait<0>();
          } else {
            wgmma_fence();
#pragma unroll
            for (int k = 0; k < 8; k++) WgmmaSS<8, 1, 0>::mma(cs, mkdesc(ad + DMN + k * 128), (uint64_t)((SB + ONES_OFF) >> 4), 1);
            wgmma_commit();
            wgmma_wait<0>();
          }
          if ((threadIdx.x & 127) < CLUSTER) mbar_arrive(bars + PEMPTY + s * 8);
          if (++s == O_STAGES) { s = 0; ph ^= 1; }
        }
        fence_regs(cs);
        if (q < 2) st_tagged(&g_cs[b * 128 + wg * 64 + w4 * 16 + q * 8 + r8], q ? cs[2] : cs[0], ep);
        TSTAMP_WG(8 + (u >> 2));
      }
      cluster_sync_relaxed();
      return;
    }
    uint32_t raw_par[3];
    {
      const int p = min((wg * 8 + role) * 64 + w4 * 16 + (lane & 15), P_ - 1);
      asm volatile("ld.global.nc.u16 %0, [%1];" : "=r"(raw_par[0]) : "l"(ptrs.lam_re + p));
      asm volatile("ld.global.nc.u16 %0, [%1];" : "=r"(raw_par[1]) : "l"(ptrs.lam_im + p));
      asm volatile("ld.global.nc.u16 %0, [%1];" : "=r"(raw_par[2]) : "l"(ptrs.log_dt + p));
    }

    const bool rel = (threadIdx.x & 127) < CLUSTER;
    uint32_t rbars;
    asm volatile("mapa.shared::cluster.u32 %0, %1, %2;" : "=r"(rbars) : "r"(bars), "r"(threadIdx.x & 1));

    const int lane_rel = (threadIdx.x & 127) / CLUSTER;
    const uint32_t prel = rbars + PEMPTY + (lane_rel & 7) * 8;

    float acc[2][64];
    auto mma_half = [&](auto isb_tag, uint32_t xd, uint32_t wd, int k0, bool accum) {
      constexpr bool ISB = decltype(isb_tag)::value;
#pragma unroll
      for (int k = k0; k < k0 + 2; k++) {
        if constexpr (ISB) {
          WgmmaSS<128, 0, 0>::mma(acc[0], mkdesc(wd + k * 2), mkdesc(xd + k * 2), accum || k);
          WgmmaSS<128, 0, 0>::mma(acc[1], mkdesc(wd + 512 + k * 2), mkdesc(xd + k * 2), accum || k);
        } else {
          WgmmaSS<128, 0, 1>::mma(acc[0], mkdesc(xd + k * 2), mkdesc(wd + k * 128), accum || k);
          WgmmaSS<128, 0, 1>::mma(acc[1], mkdesc(xd + 512 + k * 2), mkdesc(wd + k * 128), accum || k);
        }
      }
    };
    auto mainloop = [&](auto isb_tag, int j) {
      constexpr bool ISB = decltype(isb_tag)::value;
      constexpr uint32_t XD0 = (SB >> 4) + DK, WD0 = ((SB + WRING_OFF) >> 4) + (ISB ? DK : DMN);
      constexpr uint32_t WD_X = 0x1800, F_X = 0x30, E_X = 0xf0;
      static_assert(O_LEAD <= 4 && Y_LEAD <= 4, "the streamed segment must release every stage that is refilled");
      static_assert((WD0 ^ WD_X) == WD0 + 2048 && ((WD0 + 1024) ^ WD_X) == WD0 + 3072, "ring layout");
      static_assert((WFULL ^ F_X) == WFULL + 16 && ((WFULL + 8) ^ F_X) == WFULL + 24 && (WEMPTY ^ E_X) == WEMPTY + 16 && ((WEMPTY + 8) ^ E_X) == WEMPTY + 24, "barrier layout");
      const int s0 = j < 2 ? 1 - j : (j & 1) * 2;
      uint32_t wd = WD0 + s0 * 1024, fb = bars + WFULL + s0 * 8, eb = rbars + WEMPTY + s0 * 8;
      uint32_t xd = XD0;
      if (j < 2) {
        TSTAMP_WG(8 + j * 4);
        uint32_t xb = bars + XFULL;
#pragma unroll 1
        for (int kb = 0; kb < 10; kb++) {
          mbar_wait(xb, 0);
          mbar_wait(fb, (kb >> 1) & 1);
          TRACE(128 + j * 10 + kb);
          wgmma_fence();
          mma_half(isb_tag, xd, wd, 0, kb != 0);
          mma_half(isb_tag, xd, wd, 2, true);
          wgmma_commit();
          if (ISB) bar_arrive_if(kb == 9, NB_ORDER + 1);
          wgmma_wait<0>();
          arrive_if(rel, eb);
          xd += 1024; xb += 8; wd ^= WD_X; fb ^= F_X; eb ^= E_X;
        }
      } else {
        uint32_t pair = j * 5;
        int trig = (j == njobs - 1 && lane_rel < (is_y ? 2 : 3)) ? 3 : -1;
        asm volatile("" : "+r"(wd), "+r"(fb), "+r"(eb), "+r"(pair), "+r"(trig));
        peek_clear();
        bar_sync(NB_ORDER + wg, 256);
        TSTAMP_WG(8 + j * 4);
#pragma unroll 1
        for (int i = 0; i < 5; i++) {
          const uint32_t par = (pair >> 1) & 1;
          pair++;
          wait_peeked(fb, par);
          TRACE(128 + j * 10 + 2 * i);
          wgmma_fence();
          mma_half(isb_tag, xd, wd, 0, i != 0);
          wgmma_commit();
          wgmma_wait<1>();
          arrive_if(rel && i != 0, (eb ^ E_X) + 8);
          peek(fb + 8, par);
          arrive_if(i == trig, prel);
          mma_half(isb_tag, xd, wd, 2, true);
          wgmma_commit();
          wait_peeked(fb + 8, par);
          TRACE(128 + j * 10 + 2 * i + 1);
          wgmma_fence();
          mma_half(isb_tag, xd + 1024, wd + 1024, 0, true);
          wgmma_commit();
          wgmma_wait<1>();
          arrive_if(rel, eb);
          fb ^= F_X; eb ^= E_X;
          peek(fb, (pair >> 1) & 1);
          mma_half(isb_tag, xd + 1024, wd + 1024, 2, true);
          wgmma_commit();
          xd += 2048; wd ^= WD_X;
        }
        bar_arrive_if(j != njobs - 1, NB_ORDER + (wg ^ 1));
        wgmma_wait<0>();
        arrive_if(rel, (eb ^ E_X) + 8);
        arrive_if(j >= njobs - 2 && trig < 0 && lane_rel < (is_y ? Y_STAGES : O_STAGES), prel);
      }
      fence_regs(acc[0]); fence_regs(acc[1]);
      TSTAMP_WG(8 + j * 4 + 1);
    };

    const int slab = wg * 4 + w4;
    const int c0 = is_y ? (role == 2 ? D_ - YN : role * YN) : (role - 3) * 128;
    uint32_t xr[2][16];
#pragma unroll
    for (int i = 0; i < 16; i++) { xr[0][i] = 0; xr[1][i] = 0; }
#pragma unroll 1
    for (int j = wg; j < njobs; j = wg ? j * 2 : j + 3) {
    const int b = job_block(j, role);
    if (b < 10) {
      mainloop(BoolTag<true>{}, j);
      cplx lam, cf;
      asm volatile("" : "+r"(raw_par[0]), "+r"(raw_par[1]), "+r"(raw_par[2]));
      ssm_params(bf_lo(raw_par[0]), bf_lo(raw_par[1]), bf_lo(raw_par[2]), lam, cf);
      cplx lamA = cshfl(lam, r8), lamB = cshfl(lam, r8 + 8);
      bar_sync(NB_CS + wg, 160);
      const uint32_t ep = lds_volatile(bars + EPOCH);
      const int pA = b * 64 + w4 * 16 + r8;
      const cplx csA = {s_cs[w4 * 16 + r8], s_cs[64 + w4 * 16 + r8]}, csB = {s_cs[w4 * 16 + r8 + 8], s_cs[64 + w4 * 16 + r8 + 8]};
      cplx aA = {0.f, 0.f}, aB = {0.f, 0.f};
#pragma unroll
      for (int i = 0; i < 16; i++) {
        const float4 st = *reinterpret_cast<const float4*>(s_stat + 8 * i + 2 * q);
#pragma unroll
        for (int e = 0; e < 2; e++) {
          float mb = e ? st.z : st.x;
          const float rd = e ? st.w : st.y;
          if ((YB & 1) || ((YB & 8) && e == 0)) yield_slot(ptrs.zero, ptrs.zero, __float_as_uint(aA.r), mb, aB.r);
          const int ia = 4 * i + e, ib = ia + 2;
          acc[0][ia] = fmaf(mb, csA.r, acc[0][ia]) * rd; acc[1][ia] = fmaf(mb, csA.i, acc[1][ia]) * rd;
          acc[0][ib] = fmaf(mb, csB.r, acc[0][ib]) * rd; acc[1][ib] = fmaf(mb, csB.i, acc[1][ib]) * rd;
          aA = cfma(lamA, aA, cplx{acc[0][ia], acc[1][ia]});
          aB = cfma(lamB, aB, cplx{acc[0][ib], acc[1][ib]});
        }
      }
      cplx l32A = lamA, l32B = lamB;
#pragma unroll
      for (int i = 0; i < 5; i++) { l32A = cmul(l32A, l32A); l32B = cmul(l32B, l32B); }
      const int qb = lane & ~3;
      cplx eA, eB;
      {
        cplx a0 = cshfl(aA, qb), a1 = cshfl(aA, qb + 1), a2 = cshfl(aA, qb + 2), a3 = cshfl(aA, qb + 3);
        cplx e2 = cfma(l32A, a0, a1), e3 = cfma(l32A, e2, a2);
        aA = cfma(l32A, e3, a3);
        eA = csel(q < 2, csel(q == 0, cplx{0.f, 0.f}, a0), csel(q == 2, e2, e3));
        a0 = cshfl(aB, qb); a1 = cshfl(aB, qb + 1); a2 = cshfl(aB, qb + 2); a3 = cshfl(aB, qb + 3);
        e2 = cfma(l32B, a0, a1); e3 = cfma(l32B, e2, a2);
        aB = cfma(l32B, e3, a3);
        eB = csel(q < 2, csel(q == 0, cplx{0.f, 0.f}, a0), csel(q == 2, e2, e3));
      }
      if (q < 2 && m < 15) {
        const cplx a = csel(q == 0, aA, aB);
        const uint64_t w0 = (uint64_t)__float_as_uint(a.r) | ((uint64_t)ep << 32), w1 = (uint64_t)__float_as_uint(a.i) | ((uint64_t)ep << 32);
        asm volatile("st.relaxed.gpu.global.v2.u64 [%0], {%1, %2};" :: "l"(&g_agg[m * P_ + pA + q * 8]), "l"(w0), "l"(w1) : "memory");
      }
      TSTAMP_WG(6 + wg);
      cplx cfA = cshfl(cf, r8), cfB = cshfl(cf, r8 + 8);
#pragma unroll
      for (int i = 0; i < 16; i++) {
#pragma unroll
        for (int e = 0; e < 2; e++) {
          const cplx ta = cmulc(cfA, cplx{acc[0][4 * i + e], acc[1][4 * i + e]});
          const cplx tb = cmulc(cfB, cplx{acc[0][4 * i + 2 + e], acc[1][4 * i + 2 + e]});
          acc[0][4 * i + e] = ta.r; acc[1][4 * i + e] = ta.i; acc[0][4 * i + 2 + e] = tb.r; acc[1][4 * i + 2 + e] = tb.i;
        }
        if (YB & 2) yield_slot(ptrs.zero, ptrs.zero, __float_as_uint(acc[1][4 * i + 3]), cfA.i, cfB.i);
      }
      fence_regs(acc[0]); fence_regs(acc[1]);
      const cplx l64A = cmul(l32A, l32A), l64B = cmul(l32B, l32B);
      const cplx l128A = cmul(l64A, l64A), l128B = cmul(l64B, l64B);
      const cplx l256A = cmul(l128A, l128A), l256B = cmul(l128B, l128B);
      const cplx l512A = cmul(l256A, l256A), l512B = cmul(l256B, l256B);
      cplx gA = {0.f, 0.f}, gB = {0.f, 0.f};
      {
        uint4 vA[4], vB[4];
        const uint32_t t0 = clock32();
        bool ok;
        do {
          ok = true;
#pragma unroll
          for (int t = 0; t < 4; t++) {
            const int jt = m - 1 - q - 4 * t;
            vA[t] = make_uint4(0u, ep, 0u, ep); vB[t] = vA[t];
            if (jt >= 0) { vA[t] = ld_relaxed128(&g_agg[jt * P_ + pA]); vB[t] = ld_relaxed128(&g_agg[jt * P_ + pA + 8]); }
          }
#pragma unroll
          for (int t = 0; t < 4; t++) ok = ok && vA[t].y == ep && vA[t].w == ep && vB[t].y == ep && vB[t].w == ep;
          ok = ok || clock32() - t0 > 1000000000u;
        } while (!__all_sync(0xffffffffu, ok));
#pragma unroll
        for (int t = 3; t >= 0; t--) {
          gA = cfma(l512A, gA, cplx{__uint_as_float(vA[t].x), __uint_as_float(vA[t].z)});
          gB = cfma(l512B, gB, cplx{__uint_as_float(vB[t].x), __uint_as_float(vB[t].z)});
        }
      }
      {
        const cplx one = {1.f, 0.f};
        gA = cmul(gA, csel(q < 2, csel(q == 0, one, l128A), csel(q == 2, l256A, cmul(l256A, l128A))));
        gB = cmul(gB, csel(q < 2, csel(q == 0, one, l128B), csel(q == 2, l256B, cmul(l256B, l128B))));
#pragma unroll
        for (int o = 1; o < 4; o <<= 1) {
          gA.r += __shfl_xor_sync(0xffffffffu, gA.r, o); gA.i += __shfl_xor_sync(0xffffffffu, gA.i, o);
          gB.r += __shfl_xor_sync(0xffffffffu, gB.r, o); gB.i += __shfl_xor_sync(0xffffffffu, gB.i, o);
        }
        gA = cfma(gA, csel(q < 2, csel(q == 0, one, l32A), csel(q == 2, l64A, cmul(l64A, l32A))), eA);
        gB = cfma(gB, csel(q < 2, csel(q == 0, one, l32B), csel(q == 2, l64B, cmul(l64B, l32B))), eB);
        gA = cmulc(gA, cfA); gB = cmulc(gB, cfB);
        lamA.i = -lamA.i; lamB.i = -lamB.i;
      }
      TSTAMP_WG(8 + j * 4 + 2);
      __nv_bfloat16* hp = g_hT + (size_t)pA * L_ + m * 128 + q * 8;
#pragma unroll
      for (int c = 0; c < 4; c++) {
        uint32_t oAr[4], oAi[4], oBr[4], oBi[4];
#pragma unroll
        for (int ii = 0; ii < 4; ii++) {
          const int i = c * 4 + ii;
          const cplx a0 = cfma(lamA, gA, cplx{acc[0][4 * i], acc[1][4 * i]});
          const cplx b0 = cfma(lamB, gB, cplx{acc[0][4 * i + 2], acc[1][4 * i + 2]});
          gA = cfma(lamA, a0, cplx{acc[0][4 * i + 1], acc[1][4 * i + 1]});
          gB = cfma(lamB, b0, cplx{acc[0][4 * i + 3], acc[1][4 * i + 3]});
          oAr[ii] = pack_bf16(a0.r, gA.r); oAi[ii] = pack_bf16(a0.i, gA.i);
          oBr[ii] = pack_bf16(b0.r, gB.r); oBi[ii] = pack_bf16(b0.i, gB.i);
          if (YB & 4) yield_slot(ptrs.zero, ptrs.zero, oBi[ii], gA.i, gB.i);
        }
        stg128(hp + c * 32, oAr[0], oAr[1], oAr[2], oAr[3]);
        stg128(hp + c * 32 + 8 * L_, oBr[0], oBr[1], oBr[2], oBr[3]);
        stg128(hp + c * 32 + P_ * L_, oAi[0], oAi[1], oAi[2], oAi[3]);
        stg128(hp + c * 32 + (P_ + 8) * L_, oBi[0], oBi[1], oBi[2], oBi[3]);
      }
#pragma unroll
      for (int i = 0; i < 16; i++) { asm volatile("mov.b32 %0, 0;" : "=r"(xr[0][i])); asm volatile("mov.b32 %0, 0;" : "=r"(xr[1][i])); }
    } else {
      if (j >= 3 && !is_y) {
        int ln = lane;
        asm volatile("" : "+r"(ln));
        const int rho = (ln & 1) + 4 * (slab & 1) + ((ln >> 2) & 2) + 8 * (4 * (slab >> 1) + ((ln >> 1) & 3));
        const uint32_t base = sb + (role - 3) * 2 * SLOT + rho * 128, sw = ((ln >> 4) ^ (rho & 7)) << 4;
#pragma unroll
        for (int jj = 0; jj < 16; jj += 2)
          ldsm4(xr[0][jj], xr[1][jj], xr[0][jj + 1], xr[1][jj + 1], base + (jj >> 3) * SLOT + (sw ^ ((jj & 7) << 4)));
      }
      mainloop(BoolTag<false>{}, j);
      const int ft = b - 10;
      __nv_bfloat16* hp = g_H + (size_t)(m * 128 + (w4 >> 1) * 32 + (r8 >> 1) * 8 + (w4 & 1) * 4 + (r8 & 1)) * F_ + ft * 64 + q * 8;
      bar_sync(NB_CS + wg, 160);
      TSTAMP_WG(8 + j * 4 + 2);
      const int nap = NAP && j > 1 && j < njobs - 1;
      float mb[4], k0[4], k1[4];
#pragma unroll
      for (int rr = 0; rr < 4; rr++) {
        const float2 st = s_stat[(rr >> 1) * 64 + w4 * 16 + (rr & 1) * 8 + r8];
        mb[rr] = st.x; k0[rr] = st.y * 0.7978845608028654f; k1[rr] = k0[rr] * 0.044715f * st.y * st.y;
      }
      float2 cg[4], cu[4];
      uint32_t o[4];
      float pw0 = 0.f, pw1 = 0.f, pt0 = 0.f, pt1 = 0.f;
#pragma unroll
      for (int g = 0; g <= 32; g++) {
        const int a = g >> 4, rr = (g >> 2) & 3, jj = g & 3, mi = rr >> 1, hf = rr & 1;
        float w0 = 0.f, w1 = 0.f, t0 = 0.f, t1 = 0.f;
        if (g < 32) {
          if (rr == 0) {
            cg[jj] = *reinterpret_cast<const float2*>(s_cs + (a * 4 + jj) * 8 + q * 2);
            cu[jj] = *reinterpret_cast<const float2*>(s_cs + 64 + (a * 4 + jj) * 8 + q * 2);
          }
          const int i0 = 4 * (a * 4 + jj) + hf * 2;
          const float g0 = fmaf(mb[rr], cg[jj].x, acc[mi][i0]), g1 = fmaf(mb[rr], cg[jj].y, acc[mi][i0 + 1]);
          w0 = g0 * fmaf(mb[rr], cu[jj].x, acc[mi][32 + i0]); w1 = g1 * fmaf(mb[rr], cu[jj].y, acc[mi][32 + i0 + 1]);
          t0 = tanh_fast(g0 * fmaf(g0 * g0, k1[rr], k0[rr])); t1 = tanh_fast(g1 * fmaf(g1 * g1, k1[rr], k0[rr]));
        }
        if (g > 0) {
          const int p = g - 1, pa = p >> 4, prr = (p >> 2) & 3, pj = p & 3;
          o[pj] = pack_bf16(fmaf(pw0, pt0, pw0), fmaf(pw1, pt1, pw1));
          if (pj == 3) stg128(hp + ((prr >> 1) * 64 + (prr & 1) * 2) * F_ + pa * 32, o[0], o[1], o[2], o[3]);
          if (g < 32 && (YU == 1 || (YU == 2 && (g & 1)))) yield_slot((NAP == 1 || (NAP == 2 && (g & 1))) ? nap : ptrs.zero, ptrs.zero, o[pj], mb[((g + 1) >> 2) & 3], t1);
        }
        pw0 = w0; pw1 = w1; pt0 = t0; pt1 = t1;
      }
    }
    bar_arrive(NB_FLAG + wg, 160);
    TSTAMP_WG(8 + j * 4 + 3);
    }

    TSTAMP_WG(32 + wg * 4);
    TDECL;
    peek_clear();
    if (is_y) {
      float ya[YN / 2];
      zero_regs(ya);
      uint32_t off = 0, fb = bars + PFULL, eb = 0, ph = 0;
      const uint32_t ad0 = (SB >> 4) + wg * 512 + DMN;
#pragma unroll 1
      for (int seg = 0; seg < 2; seg++) {
        if (seg == 1 && wg == 1) bar_sync(NB_LEAD, 256);
        const bool relp = rel && seg == 0;
#pragma unroll 1
        for (int n = seg ? Y_LEAD : 20 - Y_LEAD; n > 0; n--) {
          wait_peeked(fb, ph);
          const uint32_t ad = ad0 + off, wd = ((SB + SLOT) >> 4) + DK + off;
          wgmma_fence();
          WgmmaSS<YN, 1, 0>::mma(ya, mkdesc(ad), mkdesc(wd), 1);
          WgmmaSS<YN, 1, 0>::mma(ya, mkdesc(ad + 128), mkdesc(wd + 2), 1);
          wgmma_commit();
          wgmma_wait<1>();
          arrive_if(relp && eb != 0, eb);
          eb = fb + (rbars - bars) + (PEMPTY - PFULL);
          off += Y_STAGE >> 4; fb += 8;
          if (off == Y_STAGES * (Y_STAGE >> 4)) { off = 0; fb = bars + PFULL; ph ^= 1; }
          peek(fb, ph);
          WgmmaSS<YN, 1, 0>::mma(ya, mkdesc(ad + 256), mkdesc(wd + 4), 1);
          WgmmaSS<YN, 1, 0>::mma(ya, mkdesc(ad + 384), mkdesc(wd + 6), 1);
          wgmma_commit();
        }
      }
      if (wg == 0) bar_arrive(NB_LEAD, 256);
      wgmma_wait<0>();
      fence_regs(ya);
      TSTAMP_WG(32 + wg * 4 + 1);
      TDUMP(48 + wg);
      uint2* sp = g_s + ((size_t)(m * 8 + slab) * 80 + (c0 >> 3)) * 32 + lane;
#pragma unroll
      for (int jj = 0; jj < YN / 8; jj++) {
        sp[jj * 32] = make_uint2(pack_bf16(ya[4 * jj], ya[4 * jj + 1]), pack_bf16(ya[4 * jj + 2], ya[4 * jj + 3]));
      }
      bar_arrive(NB_FLAG + wg, 160);
    } else {
      float oa[64];
      zero_regs(oa);
      uint32_t xn[2][16], dk[16];
      float sc0 = 0.f, sc1 = 0.f;
      uint32_t off = 0, fb = bars + PFULL, eb = 0, ph = 0;
      const uint32_t ad0 = (SB >> 4) + wg * 512 + DK;
#pragma unroll 1
      for (int seg = 0; seg < 2; seg++) {
        if (seg == wg) {
          const int rho0 = (r8 & 1) + 4 * (slab & 1) + 8 * (4 * (slab >> 1) + (r8 >> 1));
          const float2 st0 = s_stat[rho0], st1 = s_stat[rho0 + 2];
          const uint32_t mb0 = pack_bf16(st0.x, st0.x), mb1 = pack_bf16(st1.x, st1.x);
          sc0 = 0.25f * st0.y * st0.y; sc1 = 0.25f * st1.y * st1.y;
#pragma unroll
          for (int jj = 0; jj < 16; jj++) {
            dk[jj] = ldg32(ptrs.dskip + c0 + jj * 8 + q * 2);
            const uint32_t d0 = hadd2_bf(xr[0][jj], mb0), d1 = hadd2_bf(xr[1][jj], mb1);
            xn[0][jj] = pack_bf16(bf_lo(d0) * st0.y, bf_hi(d0) * st0.y);
            xn[1][jj] = pack_bf16(bf_lo(d1) * st1.y, bf_hi(d1) * st1.y);
          }
          if (wg == 1) bar_sync(NB_LEAD, 256);
        }
        const bool relp = rel && seg == 0;
#pragma unroll 1
        for (int n = seg ? O_LEAD : 27 - O_LEAD; n > 0; n--) {
          wait_peeked(fb, ph);
          const uint32_t ad = ad0 + off, wd = ((SB + SLOT) >> 4) + DMN + off;
          const uint32_t eb_next = fb + (rbars - bars) + (PEMPTY - PFULL);
          off += O_STAGE >> 4; fb += 8;
          if (off == O_STAGES * (O_STAGE >> 4)) { off = 0; fb = bars + PFULL; ph ^= 1; }
          wgmma_fence();
          WgmmaSS<128, 0, 1>::mma(oa, mkdesc(ad), mkdesc(wd), 1);
          peek(fb, ph);
          WgmmaSS<128, 0, 1>::mma(oa, mkdesc(ad + 2), mkdesc(wd + 128), 1);
          WgmmaSS<128, 0, 1>::mma(oa, mkdesc(ad + 4), mkdesc(wd + 256), 1);
          WgmmaSS<128, 0, 1>::mma(oa, mkdesc(ad + 6), mkdesc(wd + 384), 1);
          wgmma_commit();
          wgmma_wait<1>();
          arrive_if(relp && eb != 0, eb);
          eb = eb_next;
        }
      }
      if (wg == 0) bar_arrive(NB_LEAD, 256);
      wgmma_wait<0>();
      fence_regs(oa);
      TSTAMP_WG(32 + wg * 4 + 1);
      TDUMP(48 + wg);
#pragma unroll
      for (int i = 0; i < 64; i++) {
        const float h = oa[i] * ((i & 2) ? sc1 : sc0);
        oa[i] = fmaf(h, tanh_fast(h), h);
      }
      mbar_wait(bars + PFULL + (wg ? 0 : 6 * 8), wg ? 0 : 1);
      TSTAMP_WG(32 + wg * 4 + 2);
      uint8_t* buf = smem_raw + (wg ? 0 : 6 * O_STAGE) + w4 * 8192;
      uint2 sv[16];
#pragma unroll
      for (int jj = 0; jj < 16; jj++) sv[jj] = *reinterpret_cast<const uint2*>(buf + jj * 256 + lane * 8);
      __syncwarp();
#pragma unroll
      for (int t = 0; t < 4; t++) {
#pragma unroll
        for (int j4 = 0; j4 < 4; j4++) {
          const int jj = t * 4 + j4;
          uint8_t* p = buf + t * 2048 + r8 * 128 + (((j4 * 2 + (q >> 1)) ^ r8) << 4) + (q & 1) * 8;
          const uint32_t s0 = hfma2_bf(xn[0][jj], dk[jj], sv[jj].x), s1 = hfma2_bf(xn[1][jj], dk[jj], sv[jj].y);
          *reinterpret_cast<float2*>(p) = make_float2(fmaf(bf_lo(s0), oa[4 * jj], bf_lo(xr[0][jj])), fmaf(bf_hi(s0), oa[4 * jj + 1], bf_hi(xr[0][jj])));
          *reinterpret_cast<float2*>(p + 1024) = make_float2(fmaf(bf_lo(s1), oa[4 * jj + 2], bf_lo(xr[1][jj])), fmaf(bf_hi(s1), oa[4 * jj + 3], bf_hi(xr[1][jj])));
        }
        asm volatile("fence.proxy.async.shared::cta;" ::: "memory");
        __syncwarp();
        if (elect_one()) {
          asm volatile("cp.async.bulk.tensor.5d.global.shared::cta.bulk_group [%0, {%2, %2, %3, %4, %5}], [%1];"
            :: "l"(&maps.out), "r"(smem_u32(buf) + t * 2048), "r"(0), "r"(m * 4 + (slab & 1) * 2), "r"(slab >> 1), "r"((role - 3) * 4 + t) : "memory");
        }
      }
      asm volatile("cp.async.bulk.commit_group;" ::: "memory");
      asm volatile("cp.async.bulk.wait_group.read 0;" ::: "memory");
      __syncwarp();
    }
    TSTAMP_WG(32 + wg * 4 + 3);
    cluster_sync_relaxed();
  }
}

typedef CUresult (*EncodeFn)(CUtensorMap*, CUtensorMapDataType, cuuint32_t, void*, const cuuint64_t*, const cuuint64_t*,
                             const cuuint32_t*, const cuuint32_t*, CUtensorMapInterleave, CUtensorMapSwizzle,
                             CUtensorMapL2promotion, CUtensorMapFloatOOBfill);

bool encode(EncodeFn fn, CUtensorMap* m, const void* base, int rank, const uint64_t* dims, const uint64_t* strides, const uint32_t* box,
            CUtensorMapDataType dt = CU_TENSOR_MAP_DATA_TYPE_BFLOAT16) {
  cuuint64_t d[5], s[5]; cuuint32_t b[5], e[5];
  for (int i = 0; i < rank; i++) { d[i] = dims[i]; b[i] = box[i]; e[i] = 1; if (i + 1 < rank) s[i] = strides[i]; }
  CUresult r = fn(m, dt, rank, const_cast<void*>(base), d, s, b, e, CU_TENSOR_MAP_INTERLEAVE_NONE,
                  CU_TENSOR_MAP_SWIZZLE_128B, CU_TENSOR_MAP_L2_PROMOTION_L2_256B, CU_TENSOR_MAP_FLOAT_OOB_FILL_NONE);
  if (r != CUDA_SUCCESS) { fprintf(stderr, "cuTensorMapEncodeTiled failed: %d\n", (int)r); return false; }
  return true;
}
bool encode2d(EncodeFn fn, CUtensorMap* m, const void* base, uint64_t inner, uint64_t outer, uint32_t box_outer) {
  const uint64_t dims[2] = {inner, outer}, str[1] = {inner * 2};
  const uint32_t box[2] = {64, box_outer};
  return encode(fn, m, base, 2, dims, str, box);
}

}

extern "C" void kernel_launch(void* const* d_in, const int* in_sizes, int n_in, void* d_out, int out_size) {
  (void)in_sizes; (void)n_in; (void)out_size;
  static EncodeFn fn = nullptr;
  if (!fn) {
    void* p = nullptr; cudaDriverEntryPointQueryResult st;
    if (cudaGetDriverEntryPoint("cuTensorMapEncodeTiled", &p, cudaEnableDefault, &st) != cudaSuccess || !p) { fprintf(stderr, "no cuTensorMapEncodeTiled\n"); return; }
    fn = (EncodeFn)p;
    cudaFuncSetAttribute(fused_kernel, cudaFuncAttributeMaxDynamicSharedMemorySize, SMEM_BYTES);
  }
  void *H, *hT;
  cudaGetSymbolAddress(&H, g_H); cudaGetSymbolAddress(&hT, g_hT);
  Maps maps;
  bool ok = true;
  {
    const uint64_t dims[4] = {D_, 2, L_ / 32, 16}, str[3] = {D_ * 2, 32 * D_ * 2, 2 * D_ * 2};
    const uint32_t box[4] = {64, 2, 4, 16};
    ok &= encode(fn, &maps.x, d_in[0], 4, dims, str, box);
  }
  ok &= encode2d(fn, &maps.bre, d_in[3], D_, P_, 64);
  ok &= encode2d(fn, &maps.bim, d_in[4], D_, P_, 64);
  ok &= encode2d(fn, &maps.wg, d_in[10], F_, D_, 64);
  ok &= encode2d(fn, &maps.wu, d_in[11], F_, D_, 64);
  ok &= encode2d(fn, &maps.h, H, F_, L_, 128);
  {
    const uint64_t dims[5] = {D_, 2, 4, 4, F_ / 32}, str[4] = {D_ * 2, 8 * D_ * 2, 2 * D_ * 2, 32 * D_ * 2};
    const uint32_t box[5] = {64, 2, 4, 4, 2};
    ok &= encode(fn, &maps.wd, d_in[12], 5, dims, str, box);
  }
  {
    const uint64_t dims[3] = {64, 2 * P_, L_ / 64}, str[2] = {L_ * 2, 128};
    const uint32_t box[3] = {64, 64, 2};
    ok &= encode(fn, &maps.ht, hT, 3, dims, str, box);
  }
  ok &= encode2d(fn, &maps.cre0, d_in[5], P_, D_, 112);
  ok &= encode2d(fn, &maps.cre1, d_in[5], P_, D_, 104);
  ok &= encode2d(fn, &maps.cim0, d_in[6], P_, D_, 112);
  ok &= encode2d(fn, &maps.cim1, d_in[6], P_, D_, 104);
  {
    const uint64_t dims[5] = {32, 8, L_ / 32, 4, D_ / 32}, str[4] = {D_ * 4, 32 * D_ * 4, 8 * D_ * 4, 128};
    const uint32_t box[5] = {32, 8, 2, 1, 1};
    ok &= encode(fn, &maps.out, d_out, 5, dims, str, box, CU_TENSOR_MAP_DATA_TYPE_FLOAT32);
  }
  if (!ok) return;

  cudaLaunchConfig_t cfg = {};
  cfg.gridDim = dim3(NCTA); cfg.blockDim = dim3(384); cfg.dynamicSmemBytes = SMEM_BYTES; cfg.stream = cudaStreamPerThread;
  cudaLaunchAttribute at[1];
  at[0].id = cudaLaunchAttributeClusterDimension; at[0].val.clusterDim.x = CLUSTER; at[0].val.clusterDim.y = 1; at[0].val.clusterDim.z = 1;
  cfg.attrs = at; cfg.numAttrs = CLUSTER > 1 ? 1 : 0;
  typedef const __nv_bfloat16* BP;
  const Ptrs ptrs = {(BP)d_in[0], (BP)d_in[1], (BP)d_in[2], (BP)d_in[7], (BP)d_in[8], (BP)d_in[3], (BP)d_in[4], (BP)d_in[5], (BP)d_in[6], (BP)d_in[12], 0};
  cudaLaunchKernelEx(&cfg, fused_kernel, maps, ptrs);
}
```

```cpp
#include <cuda_runtime.h>
#include <cuda_bf16.h>
#include <cuda.h>
#include <stdint.h>
#include <stdio.h>

#define CLUSTER 2
#define TIMING 0

namespace {

constexpr int L_ = 2048, D_ = 640, P_ = 640, F_ = 1728;
constexpr int NSPARE = 4;
constexpr int NCTA = 128 + NSPARE;
constexpr int SLOT = 16384;
constexpr int WRING_OFF = 10 * SLOT;
constexpr int BAR_OFF = 14 * SLOT;
constexpr int STAT_OFF = BAR_OFF + 320;
constexpr int CS_OFF = STAT_OFF + 1024;
constexpr int ONES_OFF = CS_OFF + 1024;
constexpr int LAM_OFF = ONES_OFF + 128;
constexpr int SMEM_BYTES = LAM_OFF + 512;
constexpr uint32_t SB = 0x400;
constexpr int YN0 = 208, YN2 = 224;
constexpr int Y_STAGE = SLOT + YN2 * 128;
constexpr int Y_STAGES = 5;
constexpr int O_STAGE = 2 * SLOT;
constexpr int O_STAGES = 6;
constexpr int S_STAGES = 7;
#define PREFETCH 3
#define NOSTORE 0
#define PACE 0
#define YB 6
#define YU 3
#define NAP 64
#define DRY 0
#define ZINIT 0
#define A_LEAD 0
#define MAPPING 1
#define INPLACE 0
#define BDELAY 0
#define PRE_SILU 1
#define PF0 0
#define PF1 0
#define O_SOLO 11
#define YS 1
#define O_RUN 3
#define NAPX 32
#define NAP3 32
#define X_AHEAD 3
#define Y_LEAD 4
#define O_LEAD 4

__device__ __nv_bfloat16 g_H[L_ * F_];
__device__ __nv_bfloat16 g_hT[2 * P_ * L_];
__device__ uint4 g_s[L_ * D_ / 8];
__device__ uint4 g_agg[16 * P_];
__device__ uint2 g_cs[37 * 128];
__device__ uint2 g_stat[L_];
__device__ uint4 g_kc[128 * 7 * 128];
__device__ uint32_t g_ticket;
__device__ uint32_t g_flag[16 * 32];

struct Maps {
  CUtensorMap x, bre, bim, wg, wu, h, wd, ht, cre0, cre1, cim0, cim1, cre2, cim2, out;
};

__device__ __forceinline__ uint32_t smem_u32(const void* p) { return (uint32_t)__cvta_generic_to_shared(p); }
__device__ __forceinline__ void mbar_init(uint32_t bar, uint32_t count) { asm volatile("mbarrier.init.shared::cta.b64 [%0], %1;" :: "r"(bar), "r"(count) : "memory"); }
__device__ __forceinline__ void mbar_expect_tx(uint32_t bar, uint32_t bytes) { asm volatile("mbarrier.arrive.expect_tx.shared::cta.b64 _, [%0], %1;" :: "r"(bar), "r"(bytes) : "memory"); }
__device__ __forceinline__ void mbar_arrive(uint32_t bar) { asm volatile("mbarrier.arrive.shared::cta.b64 _, [%0];" :: "r"(bar) : "memory"); }
__device__ __forceinline__ void mbar_arrive_cluster(uint32_t bar, uint32_t cta) {
  asm volatile("{\n.reg .b32 ra;\nmapa.shared::cluster.u32 ra, %0, %1;\nmbarrier.arrive.shared::cluster.b64 _, [ra];\n}" :: "r"(bar), "r"(cta) : "memory");
}
__device__ __forceinline__ void mbar_wait(uint32_t bar, uint32_t parity) {
  asm volatile("{\n.reg .pred p;\n.reg .u32 t0, t1;\n"
    "mbarrier.try_wait.parity.shared::cta.b64 p, [%0], %1;\n@p bra LAB_DONE;\n"
    "mov.u32 t0, %%clock;\n"
    "LAB_WAIT:\n"
    "mbarrier.try_wait.parity.shared::cta.b64 p, [%0], %1;\n@p bra LAB_DONE;\n"
    "mov.u32 t1, %%clock;\nsub.u32 t1, t1, t0;\nsetp.gt.u32 p, t1, 1000000000;\n@p trap;\nbra LAB_WAIT;\n"
    "LAB_DONE:\n}" :: "r"(bar), "r"(parity) : "memory");
}
__device__ __forceinline__ void flag_wait_ge(const uint32_t* p, uint32_t target) {
  asm volatile("{\n.reg .pred p;\n.reg .u32 t0, t1;\n.reg .s32 v;\n"
    "mov.u32 t0, %%clock;\n"
    "LAB_WAIT:\n"
    "ld.acquire.gpu.global.u32 v, [%0];\nsub.s32 v, v, %1;\nsetp.ge.s32 p, v, 0;\n@p bra LAB_DONE;\n"
    "mov.u32 t1, %%clock;\nsub.u32 t1, t1, t0;\nsetp.gt.u32 p, t1, 1000000000;\n@p trap;\nbra LAB_WAIT;\n"
    "LAB_DONE:\n}" :: "l"(p), "r"(target) : "memory");
}
__device__ __forceinline__ uint32_t ld_acquire(const uint32_t* p) { uint32_t v; asm volatile("ld.acquire.gpu.global.u32 %0, [%1];" : "=r"(v) : "l"(p) : "memory"); return v; }
__device__ __forceinline__ uint32_t ld_relaxed(const uint32_t* p) { uint32_t v; asm volatile("ld.relaxed.gpu.global.u32 %0, [%1];" : "=r"(v) : "l"(p) : "memory"); return v; }
__device__ __forceinline__ void red_release_add(uint32_t* p, uint32_t v) { asm volatile("red.release.gpu.global.add.u32 [%0], %1;" :: "l"(p), "r"(v) : "memory"); }
__device__ __forceinline__ void st_release(uint32_t* p, uint32_t v) { asm volatile("st.release.gpu.global.u32 [%0], %1;" :: "l"(p), "r"(v) : "memory"); }
__device__ __forceinline__ void fence_proxy_async() { asm volatile("fence.proxy.async.global;" ::: "memory"); }
__device__ __forceinline__ void trap_if(bool c) { asm volatile("{\n.reg .pred p;\nsetp.ne.u32 p, %0, 0;\n@p trap;\n}" :: "r"((uint32_t)c)); }
__device__ __forceinline__ uint32_t clock32() { uint32_t c; asm volatile("mov.u32 %0, %%clock;" : "=r"(c) :: "memory"); return c; }

__device__ __forceinline__ bool elect_one() {
  uint32_t p;
  asm volatile("{\n.reg .pred P;\nelect.sync _|P, 0xffffffff;\nselp.u32 %0, 1, 0, P;\n}" : "=r"(p));
  return p;
}
__device__ __forceinline__ void tma2d(uint32_t dst, const CUtensorMap* map, int c0, int c1, uint32_t bar) {
  asm volatile("cp.async.bulk.tensor.2d.shared::cluster.global.mbarrier::complete_tx::bytes [%0], [%1, {%3, %4}], [%2];"
    :: "r"(dst), "l"(map), "r"(bar), "r"(c0), "r"(c1) : "memory");
}
__device__ __forceinline__ void tma2d_mc(uint32_t dst, const CUtensorMap* map, int c0, int c1, uint32_t bar) {
  asm volatile("cp.async.bulk.tensor.2d.shared::cluster.global.mbarrier::complete_tx::bytes.multicast::cluster [%0], [%1, {%3, %4}], [%2], %5;"
    :: "r"(dst), "l"(map), "r"(bar), "r"(c0), "r"(c1), "h"((uint16_t)3) : "memory");
}
__device__ __forceinline__ void tma3d(uint32_t dst, const CUtensorMap* map, int c0, int c1, int c2, uint32_t bar) {
  asm volatile("cp.async.bulk.tensor.3d.shared::cluster.global.mbarrier::complete_tx::bytes [%0], [%1, {%3, %4, %5}], [%2];"
    :: "r"(dst), "l"(map), "r"(bar), "r"(c0), "r"(c1), "r"(c2) : "memory");
}
__device__ __forceinline__ void tma4d(uint32_t dst, const CUtensorMap* map, int c0, int c1, int c2, int c3, uint32_t bar) {
  asm volatile("cp.async.bulk.tensor.4d.shared::cluster.global.mbarrier::complete_tx::bytes [%0], [%1, {%3, %4, %5, %6}], [%2];"
    :: "r"(dst), "l"(map), "r"(bar), "r"(c0), "r"(c1), "r"(c2), "r"(c3) : "memory");
}
__device__ __forceinline__ void tma5d(uint32_t dst, const CUtensorMap* map, int c0, int c4, uint32_t bar) {
  asm volatile("cp.async.bulk.tensor.5d.shared::cluster.global.mbarrier::complete_tx::bytes [%0], [%1, {%3, %5, %5, %5, %4}], [%2];"
    :: "r"(dst), "l"(map), "r"(bar), "r"(c0), "r"(c4), "r"(0) : "memory");
}
__device__ __forceinline__ void tma5d_mc(uint32_t dst, const CUtensorMap* map, int c0, int c4, uint32_t bar) {
  asm volatile("cp.async.bulk.tensor.5d.shared::cluster.global.mbarrier::complete_tx::bytes.multicast::cluster [%0], [%1, {%3, %5, %5, %5, %4}], [%2], %6;"
    :: "r"(dst), "l"(map), "r"(bar), "r"(c0), "r"(c4), "r"(0), "h"((uint16_t)3) : "memory");
}
__device__ __forceinline__ void bulk_load(uint32_t dst, const void* src, uint32_t bytes, uint32_t bar) {
  asm volatile("cp.async.bulk.shared::cluster.global.mbarrier::complete_tx::bytes [%0], [%1], %2, [%3];" :: "r"(dst), "l"(src), "r"(bytes), "r"(bar) : "memory");
}
__device__ __forceinline__ void tma2d_prefetch(const CUtensorMap* map, int c0, int c1) {
  asm volatile("cp.async.bulk.prefetch.tensor.2d.L2.global [%0, {%1, %2}];" :: "l"(map), "r"(c0), "r"(c1) : "memory");
}
__device__ __forceinline__ void prefetch_l2(const void* p, uint32_t bytes) { asm volatile("cp.async.bulk.prefetch.L2.global [%0], %1;" :: "l"(p), "r"(bytes) : "memory"); }
__device__ __forceinline__ void prefetch_map(const CUtensorMap* map) { asm volatile("prefetch.tensormap [%0];" :: "l"(map) : "memory"); }
__device__ __forceinline__ void wgmma_fence() { asm volatile("wgmma.fence.sync.aligned;" ::: "memory"); }
__device__ __forceinline__ void wgmma_commit() { asm volatile("wgmma.commit_group.sync.aligned;" ::: "memory"); }
template<int N> __device__ __forceinline__ void wgmma_wait() { asm volatile("wgmma.wait_group.sync.aligned %0;" :: "n"(N) : "memory"); }
template<int N> __device__ __forceinline__ void zero_regs(float (&d)[N]) {
#pragma unroll
  for (int i = 0; i < N; i++) asm volatile("mov.b32 %0, 0;" : "=f"(d[i]));
}
template<int N> __device__ __forceinline__ void fence_regs(float (&d)[N]) {
#pragma unroll
  for (int i = 0; i < N; i++) asm volatile("" : "+f"(d[i]) :: "memory");
}
constexpr uint32_t DK = 1u << 16, DMN = 512u << 16;
__device__ __forceinline__ uint64_t mkdesc(uint32_t lo) { return (uint64_t)lo | ((uint64_t)0x40000040u << 32); }
__device__ __forceinline__ bool mbar_try(uint32_t bar, uint32_t parity) {
  uint32_t ok;
  asm volatile("{\n.reg .pred p;\nmbarrier.test_wait.parity.shared::cta.b64 p, [%1], %2;\nselp.u32 %0, 1, 0, p;\n}" : "=r"(ok) : "r"(bar), "r"(parity) : "memory");
  return ok;
}
__device__ __forceinline__ void arrive_if(bool p, uint32_t addr) {
  asm volatile("{\n.reg .pred p;\nsetp.ne.u32 p, %0, 0;\n@p mbarrier.arrive.shared::cluster.b64 _, [%1];\n}" :: "r"((uint32_t)p), "r"(addr) : "memory");
}
__device__ __forceinline__ void peek_clear() { asm volatile("setp.ne.u32 peekp, 0, 0;" ::: "memory"); }
__device__ __forceinline__ void peek(uint32_t bar, uint32_t parity) {
  asm volatile("mbarrier.test_wait.parity.shared::cta.b64 peekp, [%0], %1;" :: "r"(bar), "r"(parity) : "memory");
}
__device__ __forceinline__ void wait_peeked(uint32_t bar, uint32_t parity) {
  asm volatile("{\n.reg .pred p;\n.reg .u32 t0, t1;\n"
    "@peekp bra LAB_DONE;\n"
    "mov.u32 t0, %%clock;\n"
    "LAB_WAIT:\n"
    "mbarrier.try_wait.parity.shared::cta.b64 p, [%0], %1;\n@p bra LAB_DONE;\n"
    "mov.u32 t1, %%clock;\nsub.u32 t1, t1, t0;\nsetp.gt.u32 p, t1, 1000000000;\n@p trap;\nbra LAB_WAIT;\n"
    "LAB_DONE:\n}" :: "r"(bar), "r"(parity) : "memory");
}
__device__ __forceinline__ uint32_t lds_volatile(uint32_t addr) { uint32_t v; asm volatile("ld.acquire.cta.shared::cta.u32 %0, [%1];" : "=r"(v) : "r"(addr) : "memory"); return v; }
__device__ __forceinline__ void sts_release(uint32_t addr, uint32_t v) { asm volatile("st.release.cta.shared::cta.u32 [%0], %1;" :: "r"(addr), "r"(v) : "memory"); }
__device__ __forceinline__ uint32_t smem_wait_bits(uint32_t addr, uint32_t mask) {
  uint32_t v;
  asm volatile("{\n.reg .pred p;\n.reg .u32 t0, t1;\n"
    "mov.u32 t0, %%clock;\n"
    "LAB_WAIT:\n"
    "ld.acquire.cta.shared::cta.u32 %0, [%1];\nand.b32 t1, %0, %2;\nsetp.ne.u32 p, t1, 0;\n@p bra LAB_DONE;\n"
    "mov.u32 t1, %%clock;\nsub.u32 t1, t1, t0;\nsetp.gt.u32 p, t1, 1000000000;\n@p trap;\nbra LAB_WAIT;\n"
    "LAB_DONE:\n}" : "=r"(v) : "r"(addr), "r"(mask) : "memory");
  return v;
}
__device__ __forceinline__ void ldsm4(uint32_t& r0, uint32_t& r1, uint32_t& r2, uint32_t& r3, uint32_t addr) {
  asm volatile("ldmatrix.sync.aligned.m8n8.x4.shared.b16 {%0,%1,%2,%3}, [%4];" : "=r"(r0), "=r"(r1), "=r"(r2), "=r"(r3) : "r"(addr) : "memory");
}
__device__ __forceinline__ void ldsm2(uint32_t& r0, uint32_t& r1, uint32_t addr) {
  asm volatile("ldmatrix.sync.aligned.m8n8.x2.shared.b16 {%0,%1}, [%2];" : "=r"(r0), "=r"(r1) : "r"(addr) : "memory");
}
__device__ __forceinline__ uint4 ld_relaxed128(const void* p) {
  uint64_t a, b;
  asm volatile("ld.relaxed.gpu.global.v2.u64 {%0, %1}, [%2];" : "=l"(a), "=l"(b) : "l"(p) : "memory");
  return make_uint4((uint32_t)a, (uint32_t)(a >> 32), (uint32_t)b, (uint32_t)(b >> 32));
}
__device__ __forceinline__ void st_tagged(void* p, float v, uint32_t tag) {
  asm volatile("st.relaxed.gpu.global.u64 [%0], %1;" :: "l"(p), "l"((uint64_t)__float_as_uint(v) | ((uint64_t)tag << 32)) : "memory");
}
__device__ __forceinline__ void cluster_sync_relaxed() {
  asm volatile("barrier.cluster.arrive.relaxed.aligned;\nbarrier.cluster.wait.aligned;" ::: "memory");
}
__device__ __forceinline__ void bar_sync(int id, int n) { asm volatile("bar.sync %0, %1;" :: "r"(id), "r"(n) : "memory"); }
__device__ __forceinline__ void bar_arrive(int id, int n) { asm volatile("bar.arrive %0, %1;" :: "r"(id), "r"(n) : "memory"); }
__device__ __forceinline__ void bar_arrive_if(bool p, int id) {
  asm volatile("{\n.reg .pred p;\nsetp.ne.u32 p, %0, 0;\n@p bar.arrive %1, 256;\n}" :: "r"((uint32_t)p), "r"(id) : "memory");
}
template<int R> __device__ __forceinline__ void reg_alloc() { asm volatile("setmaxnreg.inc.sync.aligned.u32 %0;" :: "n"(R)); }
template<int R> __device__ __forceinline__ void reg_dealloc() { asm volatile("setmaxnreg.dec.sync.aligned.u32 %0;" :: "n"(R)); }
__device__ __forceinline__ uint32_t pack_bf16(float lo, float hi) { uint32_t r; asm("cvt.rn.bf16x2.f32 %0, %1, %2;" : "=r"(r) : "f"(hi), "f"(lo)); return r; }
__device__ __forceinline__ float bf_lo(uint32_t v) { return __uint_as_float(v << 16); }
__device__ __forceinline__ float bf_hi(uint32_t v) { return __uint_as_float(v & 0xffff0000u); }
__device__ __forceinline__ float round_bf(float v) { return bf_lo(pack_bf16(v, 0.f)); }
__device__ __forceinline__ float ex2(float x) { float y; asm("ex2.approx.ftz.f32 %0, %1;" : "=f"(y) : "f"(x)); return y; }
__device__ __forceinline__ float rcp(float x) { float y; asm("rcp.approx.ftz.f32 %0, %1;" : "=f"(y) : "f"(x)); return y; }
__device__ __forceinline__ uint32_t ldg32(const void* p) { uint32_t v; asm volatile("ld.global.u32 %0, [%1];" : "=r"(v) : "l"(p) : "memory"); return v; }
__device__ __forceinline__ uint32_t hmul2_bf(uint32_t a, uint32_t b) { uint32_t r; asm("mul.rn.bf16x2 %0, %1, %2;" : "=r"(r) : "r"(a), "r"(b)); return r; }
__device__ __forceinline__ uint32_t hadd2_bf(uint32_t a, uint32_t b) { uint32_t r; asm("add.rn.bf16x2 %0, %1, %2;" : "=r"(r) : "r"(a), "r"(b)); return r; }
__device__ __forceinline__ uint32_t hfma2_bf(uint32_t a, uint32_t b, uint32_t c) { uint32_t r; asm("fma.rn.bf16x2 %0, %1, %2, %3;" : "=r"(r) : "r"(a), "r"(b), "r"(c)); return r; }
__device__ __forceinline__ void stg128_if(bool pr, void* p, uint32_t a, uint32_t b, uint32_t c, uint32_t d) {
  asm volatile("{\n.reg .pred p;\nsetp.ne.u32 p, %5, 0;\n@p st.global.v4.u32 [%0], {%1,%2,%3,%4};\n}" :: "l"(p), "r"(a), "r"(b), "r"(c), "r"(d), "r"((uint32_t)pr) : "memory");
}
__device__ __forceinline__ void stg128(void* p, uint32_t a, uint32_t b, uint32_t c, uint32_t d) { asm volatile("st.global.v4.u32 [%0], {%1,%2,%3,%4};" :: "l"(p), "r"(a), "r"(b), "r"(c), "r"(d) : "memory"); }

template<int N, int TA, int TB> struct WgmmaSS;
template<int TA, int TB> struct WgmmaSS<8, TA, TB> {
  static __device__ __forceinline__ void mma(float (&d)[4], uint64_t da, uint64_t db, int scale_d) {
    asm volatile("{\n.reg .pred p;\nsetp.ne.b32 p, %6, 0;\n"
      "wgmma.mma_async.sync.aligned.m64n8k16.f32.bf16.bf16 {"
      "%0, %1, %2, %3"
      "}, %4, %5, p, 1, 1, %7, %8;\n}\n"
      :
        "+f"(d[0]), "+f"(d[1]), "+f"(d[2]), "+f"(d[3])
      : "l"(da), "l"(db), "r"(scale_d), "n"(TA), "n"(TB));
  }
};
template<int TA, int TB> struct WgmmaSS<128, TA, TB> {
  static __device__ __forceinline__ void mma(float (&d)[64], uint64_t da, uint64_t db, int scale_d) {
    asm volatile("{\n.reg .pred p;\nsetp.ne.b32 p, %66, 0;\n"
      "wgmma.mma_async.sync.aligned.m64n128k16.f32.bf16.bf16 {"
      "%0, %1, %2, %3, %4, %5, %6, %7, %8, %9, %10, %11, %12, %13, %14, %15, "
      "%16, %17, %18, %19, %20, %21, %22, %23, %24, %25, %26, %27, %28, %29, %30, %31, "
      "%32, %33, %34, %35, %36, %37, %38, %39, %40, %41, %42, %43, %44, %45, %46, %47, "
      "%48, %49, %50, %51, %52, %53, %54, %55, %56, %57, %58, %59, %60, %61, %62, %63"
      "}, %64, %65, p, 1, 1, %67, %68;\n}\n"
      :
        "+f"(d[0]), "+f"(d[1]), "+f"(d[2]), "+f"(d[3]), "+f"(d[4]), "+f"(d[5]), "+f"(d[6]), "+f"(d[7]),
        "+f"(d[8]), "+f"(d[9]), "+f"(d[10]), "+f"(d[11]), "+f"(d[12]), "+f"(d[13]), "+f"(d[14]), "+f"(d[15]),
        "+f"(d[16]), "+f"(d[17]), "+f"(d[18]), "+f"(d[19]), "+f"(d[20]), "+f"(d[21]), "+f"(d[22]), "+f"(d[23]),
        "+f"(d[24]), "+f"(d[25]), "+f"(d[26]), "+f"(d[27]), "+f"(d[28]), "+f"(d[29]), "+f"(d[30]), "+f"(d[31]),
        "+f"(d[32]), "+f"(d[33]), "+f"(d[34]), "+f"(d[35]), "+f"(d[36]), "+f"(d[37]), "+f"(d[38]), "+f"(d[39]),
        "+f"(d[40]), "+f"(d[41]), "+f"(d[42]), "+f"(d[43]), "+f"(d[44]), "+f"(d[45]), "+f"(d[46]), "+f"(d[47]),
        "+f"(d[48]), "+f"(d[49]), "+f"(d[50]), "+f"(d[51]), "+f"(d[52]), "+f"(d[53]), "+f"(d[54]), "+f"(d[55]),
        "+f"(d[56]), "+f"(d[57]), "+f"(d[58]), "+f"(d[59]), "+f"(d[60]), "+f"(d[61]), "+f"(d[62]), "+f"(d[63])
      : "l"(da), "l"(db), "r"(scale_d), "n"(TA), "n"(TB));
  }
};
template<int TA, int TB> struct WgmmaSS<208, TA, TB> {
  static __device__ __forceinline__ void mma(float (&d)[104], uint64_t da, uint64_t db, int scale_d) {
    asm volatile("{\n.reg .pred p;\nsetp.ne.b32 p, %106, 0;\n"
      "wgmma.mma_async.sync.aligned.m64n208k16.f32.bf16.bf16 {"
      "%0, %1, %2, %3, %4, %5, %6, %7, %8, %9, %10, %11, %12, %13, %14, %15, "
      "%16, %17, %18, %19, %20, %21, %22, %23, %24, %25, %26, %27, %28, %29, %30, %31, "
      "%32, %33, %34, %35, %36, %37, %38, %39, %40, %41, %42, %43, %44, %45, %46, %47, "
      "%48, %49, %50, %51, %52, %53, %54, %55, %56, %57, %58, %59, %60, %61, %62, %63, "
      "%64, %65, %66, %67, %68, %69, %70, %71, %72, %73, %74, %75, %76, %77, %78, %79, "
      "%80, %81, %82, %83, %84, %85, %86, %87, %88, %89, %90, %91, %92, %93, %94, %95, "
      "%96, %97, %98, %99, %100, %101, %102, %103"
      "}, %104, %105, p, 1, 1, %107, %108;\n}\n"
      :
        "+f"(d[0]), "+f"(d[1]), "+f"(d[2]), "+f"(d[3]), "+f"(d[4]), "+f"(d[5]), "+f"(d[6]), "+f"(d[7]),
        "+f"(d[8]), "+f"(d[9]), "+f"(d[10]), "+f"(d[11]), "+f"(d[12]), "+f"(d[13]), "+f"(d[14]), "+f"(d[15]),
        "+f"(d[16]), "+f"(d[17]), "+f"(d[18]), "+f"(d[19]), "+f"(d[20]), "+f"(d[21]), "+f"(d[22]), "+f"(d[23]),
        "+f"(d[24]), "+f"(d[25]), "+f"(d[26]), "+f"(d[27]), "+f"(d[28]), "+f"(d[29]), "+f"(d[30]), "+f"(d[31]),
        "+f"(d[32]), "+f"(d[33]), "+f"(d[34]), "+f"(d[35]), "+f"(d[36]), "+f"(d[37]), "+f"(d[38]), "+f"(d[39]),
        "+f"(d[40]), "+f"(d[41]), "+f"(d[42]), "+f"(d[43]), "+f"(d[44]), "+f"(d[45]), "+f"(d[46]), "+f"(d[47]),
        "+f"(d[48]), "+f"(d[49]), "+f"(d[50]), "+f"(d[51]), "+f"(d[52]), "+f"(d[53]), "+f"(d[54]), "+f"(d[55]),
        "+f"(d[56]), "+f"(d[57]), "+f"(d[58]), "+f"(d[59]), "+f"(d[60]), "+f"(d[61]), "+f"(d[62]), "+f"(d[63]),
        "+f"(d[64]), "+f"(d[65]), "+f"(d[66]), "+f"(d[67]), "+f"(d[68]), "+f"(d[69]), "+f"(d[70]), "+f"(d[71]),
        "+f"(d[72]), "+f"(d[73]), "+f"(d[74]), "+f"(d[75]), "+f"(d[76]), "+f"(d[77]), "+f"(d[78]), "+f"(d[79]),
        "+f"(d[80]), "+f"(d[81]), "+f"(d[82]), "+f"(d[83]), "+f"(d[84]), "+f"(d[85]), "+f"(d[86]), "+f"(d[87]),
        "+f"(d[88]), "+f"(d[89]), "+f"(d[90]), "+f"(d[91]), "+f"(d[92]), "+f"(d[93]), "+f"(d[94]), "+f"(d[95]),
        "+f"(d[96]), "+f"(d[97]), "+f"(d[98]), "+f"(d[99]), "+f"(d[100]), "+f"(d[101]), "+f"(d[102]), "+f"(d[103])
      : "l"(da), "l"(db), "r"(scale_d), "n"(TA), "n"(TB));
  }
};
template<int TA, int TB> struct WgmmaSS<224, TA, TB> {
  static __device__ __forceinline__ void mma(float (&d)[112], uint64_t da, uint64_t db, int scale_d) {
    asm volatile("{\n.reg .pred p;\nsetp.ne.b32 p, %114, 0;\n"
      "wgmma.mma_async.sync.aligned.m64n224k16.f32.bf16.bf16 {"
      "%0, %1, %2, %3, %4, %5, %6, %7, %8, %9, %10, %11, %12, %13, %14, %15, "
      "%16, %17, %18, %19, %20, %21, %22, %23, %24, %25, %26, %27, %28, %29, %30, %31, "
      "%32, %33, %34, %35, %36, %37, %38, %39, %40, %41, %42, %43, %44, %45, %46, %47, "
      "%48, %49, %50, %51, %52, %53, %54, %55, %56, %57, %58, %59, %60, %61, %62, %63, "
      "%64, %65, %66, %67, %68, %69, %70, %71, %72, %73, %74, %75, %76, %77, %78, %79, "
      "%80, %81, %82, %83, %84, %85, %86, %87, %88, %89, %90, %91, %92, %93, %94, %95, "
      "%96, %97, %98, %99, %100, %101, %102, %103, %104, %105, %106, %107, %108, %109, %110, %111"
      "}, %112, %113, p, 1, 1, %115, %116;\n}\n"
      :
        "+f"(d[0]), "+f"(d[1]), "+f"(d[2]), "+f"(d[3]), "+f"(d[4]), "+f"(d[5]), "+f"(d[6]), "+f"(d[7]),
        "+f"(d[8]), "+f"(d[9]), "+f"(d[10]), "+f"(d[11]), "+f"(d[12]), "+f"(d[13]), "+f"(d[14]), "+f"(d[15]),
        "+f"(d[16]), "+f"(d[17]), "+f"(d[18]), "+f"(d[19]), "+f"(d[20]), "+f"(d[21]), "+f"(d[22]), "+f"(d[23]),
        "+f"(d[24]), "+f"(d[25]), "+f"(d[26]), "+f"(d[27]), "+f"(d[28]), "+f"(d[29]), "+f"(d[30]), "+f"(d[31]),
        "+f"(d[32]), "+f"(d[33]), "+f"(d[34]), "+f"(d[35]), "+f"(d[36]), "+f"(d[37]), "+f"(d[38]), "+f"(d[39]),
        "+f"(d[40]), "+f"(d[41]), "+f"(d[42]), "+f"(d[43]), "+f"(d[44]), "+f"(d[45]), "+f"(d[46]), "+f"(d[47]),
        "+f"(d[48]), "+f"(d[49]), "+f"(d[50]), "+f"(d[51]), "+f"(d[52]), "+f"(d[53]), "+f"(d[54]), "+f"(d[55]),
        "+f"(d[56]), "+f"(d[57]), "+f"(d[58]), "+f"(d[59]), "+f"(d[60]), "+f"(d[61]), "+f"(d[62]), "+f"(d[63]),
        "+f"(d[64]), "+f"(d[65]), "+f"(d[66]), "+f"(d[67]), "+f"(d[68]), "+f"(d[69]), "+f"(d[70]), "+f"(d[71]),
        "+f"(d[72]), "+f"(d[73]), "+f"(d[74]), "+f"(d[75]), "+f"(d[76]), "+f"(d[77]), "+f"(d[78]), "+f"(d[79]),
        "+f"(d[80]), "+f"(d[81]), "+f"(d[82]), "+f"(d[83]), "+f"(d[84]), "+f"(d[85]), "+f"(d[86]), "+f"(d[87]),
        "+f"(d[88]), "+f"(d[89]), "+f"(d[90]), "+f"(d[91]), "+f"(d[92]), "+f"(d[93]), "+f"(d[94]), "+f"(d[95]),
        "+f"(d[96]), "+f"(d[97]), "+f"(d[98]), "+f"(d[99]), "+f"(d[100]), "+f"(d[101]), "+f"(d[102]), "+f"(d[103]),
        "+f"(d[104]), "+f"(d[105]), "+f"(d[106]), "+f"(d[107]), "+f"(d[108]), "+f"(d[109]), "+f"(d[110]), "+f"(d[111])
      : "l"(da), "l"(db), "r"(scale_d), "n"(TA), "n"(TB));
  }
};

#define TWAIT(stmt) stmt
#define TSTAMP_L0(slot) do {} while (0)
#define TDECL
#define TRACE(i)
#define TRACE1(i)
#define TDUMP(slot)
#define TVAL(slot, v) do {} while (0)
#define TSTAMP(slot) do {} while (0)
#define TSTAMP_WG(slot) do {} while (0)

template<int V> struct IntTag { static constexpr int value = V; };
template<bool B> struct BoolTag { static constexpr bool value = B; };
struct cplx { float r, i; };
__device__ __forceinline__ cplx cmul(cplx a, cplx b) { return {fmaf(a.r, b.r, -a.i * b.i), fmaf(a.r, b.i, a.i * b.r)}; }
__device__ __forceinline__ cplx cmulc(cplx a, cplx b) { return {fmaf(a.r, b.r, -a.i * b.i), fmaf(-a.r, b.i, -a.i * b.r)}; }
__device__ __forceinline__ cplx cfma(cplx a, cplx b, cplx c) { return {fmaf(a.r, b.r, fmaf(-a.i, b.i, c.r)), fmaf(a.r, b.i, fmaf(a.i, b.r, c.i))}; }
__device__ __forceinline__ cplx csel(bool p, cplx a, cplx b) { return {p ? a.r : b.r, p ? a.i : b.i}; }
__device__ __forceinline__ cplx cshfl(cplx a, int src) { return {__shfl_sync(0xffffffffu, a.r, src), __shfl_sync(0xffffffffu, a.i, src)}; }

__device__ __forceinline__ void yield_slot(int nap, int zero, uint32_t prev, float& root) {
  asm volatile("{\n.reg .pred p;\nsetp.eq.s32 p, %3, 0;\n@p bra.uni LAB_SKIP;\nnanosleep.u32 %3;\nlop3.b32 %0, %0, %1, %2, 0x78;\nLAB_SKIP:\n}"
    : "+f"(root) : "r"(prev), "r"(zero), "r"(nap));
}
__device__ __forceinline__ void yield_slot(int nap, int zero, uint32_t prev, float& root0, float& root1) {
  asm volatile("{\n.reg .pred p;\nsetp.eq.s32 p, %4, 0;\n@p bra.uni LAB_SKIP;\nnanosleep.u32 0;\nlop3.b32 %0, %0, %2, %3, 0x78;\nlop3.b32 %1, %1, %2, %3, 0x78;\nLAB_SKIP:\n}"
    : "+f"(root0), "+f"(root1) : "r"(prev), "r"(zero), "r"(nap));
}
__device__ __forceinline__ float tanh_fast(float x) { float y; asm("tanh.approx.f32 %0, %1;" : "=f"(y) : "f"(x)); return y; }
__device__ __forceinline__ void ssm_params(float ar, float ai, float ldt, cplx& lam, cplx& coef2) {
  const float L2E = 1.4426950408889634f;
  const float dt = round_bf(ex2(ldt * L2E));
  const float xr = dt * ar, th = dt * ai;
  const float hi = xr * L2E, lo = fmaf(xr, L2E, -hi) + xr * 1.925963033500011e-8f;
  const float e = ex2(hi) * fmaf(lo, 0.6931471805599453f, 1.0f);
  const float kf = rintf(th * 0.6366197723675814f);
  float r = fmaf(kf, -1.5707963705062866f, th);
  r = fmaf(kf, 4.371138828673793e-8f, r);
  r = fmaf(kf, 1.7151245100058819e-15f, r);
  const int k = (int)kf;
  const float r2 = r * r;
  float sp = fmaf(r2, -1.9515295891e-4f, 8.3321608736e-3f); sp = fmaf(sp, r2, -1.6666654611e-1f); sp = fmaf(sp * r2, r, r);
  float cp = fmaf(r2, 2.443315711809948e-5f, -1.388731625493765e-3f); cp = fmaf(cp, r2, 4.166664568298827e-2f); cp = fmaf(cp, r2, -0.5f); cp = fmaf(cp, r2, 1.0f);
  float sn = (k & 1) ? cp : sp, cs = (k & 1) ? sp : cp;
  sn = (k & 2) ? -sn : sn; cs = ((k + 1) & 2) ? -cs : cs;
  lam.r = e * cs; lam.i = e * sn;
  const bool sw = fabsf(ar) < fabsf(ai);
  const float p = sw ? ai : ar, qq = sw ? ar : ai;
  const float nr = lam.r - 1.0f, ni = lam.i;
  const float t = __fdividef(qq, p), id = __fdividef(2.0f, fmaf(qq, t, p));
  coef2.r = (sw ? fmaf(nr, t, ni) : fmaf(ni, t, nr)) * id;
  coef2.i = (sw ? fmaf(ni, t, -nr) : fmaf(-nr, t, ni)) * id;
}

constexpr uint32_t XFULL = 0, WFULL = 80, WEMPTY = 112, PFULL = 144, PEMPTY = 200, EPOCH = 256, READY = 260;
constexpr int NB_WG0 = 1, NB_ORDER = 2  , NB_FLAG = 4  , NB_CS = 6  , NB_LEAD = 8, NB_HAND = 9, NB_WG1 = 10;

struct Ptrs { const __nv_bfloat16 *x, *lam_re, *lam_im, *log_dt, *dskip, *bre, *bim, *cre, *cim, *wd; int zero; };

__device__ __forceinline__ int job_block(int j, int role) {
  return role + (j < 4 ? j * 8 : 29);
}

__global__ void __launch_bounds__(384, 1) fused_kernel(const __grid_constant__ Maps maps, const Ptrs ptrs) {
  extern __shared__ __align__(1024) uint8_t smem_raw[];
  asm volatile(".reg .pred peekp;");
  const int warp = __shfl_sync(0xffffffffu, threadIdx.x >> 5, 0);
  const int lane = threadIdx.x & 31;
  const bool spare = blockIdx.x < NSPARE;
  const int spare_id = blockIdx.x;
  const int cta = (int)blockIdx.x - NSPARE;
  const int m = (cta + 12) & 15;
  const int role = (((cta + 124) >> 4) + 3) & 7;
  const int rank = blockIdx.x & 1;
  const bool is_y = role < 3;
  const int njobs = is_y ? 4 : 5;

  uint32_t sb = smem_u32(smem_raw);
  asm volatile("mov.u32 %0, %0;" : "+r"(sb));
  const uint32_t bars = sb + BAR_OFF;

  if (warp == 8) {
    if (elect_one()) {
      TSTAMP(0);
      TRACE1(127);
#pragma unroll
      for (int i = 0; i < 14; i++) mbar_init(bars + i * 8, 1);
      asm volatile("fence.mbarrier_init.release.cluster;" ::: "memory");
      if (!spare) {
        mbar_expect_tx(bars + XFULL, SLOT);
        tma4d(sb, &maps.x, 0, 0, m * 4, 0, bars + XFULL);
        mbar_expect_tx(bars + WFULL, SLOT);
        tma2d(sb + WRING_OFF, &maps.bre, 0, role * 64, bars + WFULL);
        tma2d(sb + WRING_OFF + 8192, &maps.bim, 0, role * 64, bars + WFULL);
      }
      TSTAMP(50);
    }
    __syncwarp();
  } else if (warp == 9) {
    trap_if((sb & 0xffffffu) != SB);
    if (elect_one()) {
#pragma unroll
      for (int i = 14; i < 32; i++) mbar_init(bars + i * 8, i < 18 ? CLUSTER : i < 25 ? 1 : 2 * CLUSTER);
      asm volatile("st.shared.v2.u32 [%0], {0, 0};" :: "r"(bars + EPOCH) : "memory");
      asm volatile("fence.mbarrier_init.release.cluster;" ::: "memory");
    }
    __syncwarp();
  } else if (warp == 10) {
    asm volatile("st.shared.u32 [%0], %1;" :: "r"(sb + ONES_OFF + lane * 4), "r"(0x3f803f80u) : "memory");
    asm volatile("fence.proxy.async.shared::cta;" ::: "memory");
  }
  __syncthreads();
  cluster_sync_relaxed();
  if (threadIdx.x == 0) TSTAMP(54);

  if (warp >= 8) {
    reg_dealloc<40>();
    if (spare) {
      if (warp == 8) {
        int s = 0; uint32_t ph = 1;
#pragma unroll 1
        for (int u = spare_id; u < 27; u += NSPARE) {
#pragma unroll 1
          for (int kb = 0; kb < 5; kb++) {
            mbar_wait(bars + PEMPTY + s * 8, ph);
            if (elect_one()) {
              mbar_expect_tx(bars + PFULL + s * 8, O_STAGE);
#pragma unroll 1
              for (int i = 0; i < 4; i++) {
                tma2d(sb + s * O_STAGE + i * 8192, i & 2 ? &maps.wu : &maps.wg, u * 64, kb * 128 + (i & 1) * 64, bars + PFULL + s * 8);
              }
            }
            __syncwarp();
            if (++s == S_STAGES) { s = 0; ph ^= 1; }
          }
        }
#pragma unroll 1
        for (int i = spare_id; i < 64; i += NSPARE) {
          if (elect_one()) {
            prefetch_l2(ptrs.cre + (size_t)i * (P_ * D_ / 64), P_ * D_ * 2 / 64);
            prefetch_l2(ptrs.cim + (size_t)i * (P_ * D_ / 64), P_ * D_ * 2 / 64);
            prefetch_l2(ptrs.wd + (size_t)i * (F_ * D_ / 64), F_ * D_ * 2 / 64);
          }
          __syncwarp();
        }
      } else if (warp == 11 && lane == 0) {
        uint32_t ep;
        asm volatile("atom.relaxed.gpu.global.add.u32 %0, [%1], 1;" : "=r"(ep) : "l"(&g_ticket) : "memory");
        sts_release(bars + EPOCH, ep / NCTA + 1u);
      }
      __syncwarp();
    } else {
      if (warp == 8) {
      int j = 0, kb = 1;
#pragma unroll 1
      for (int it = 1; it < njobs * 10; it++) {
        const int b = job_block(j, role);
        const bool isB = b < 10;
        const int blk = (isB ? b : b - 10) * 64;
        const int s = it & 3;
        mbar_wait(bars + WEMPTY + s * 8, ((it >> 2) & 1) ^ 1);
        if (elect_one()) {
          if (it < 4) {
            mbar_expect_tx(bars + XFULL + it * 8, SLOT);
            tma4d(sb + it * SLOT, &maps.x, it * 64, 0, m * 4, 0, bars + XFULL + it * 8);
          }
          const uint32_t dst = sb + WRING_OFF + s * SLOT, fb = bars + WFULL + s * 8;
          const int c0 = isB ? kb * 64 : blk, c1 = isB ? blk : kb * 64;
          mbar_expect_tx(fb, SLOT);
          tma2d_mc(dst + rank * 8192, isB ? (rank ? &maps.bim : &maps.bre) : (rank ? &maps.wu : &maps.wg), c0, c1, fb);
          if (it >= 3 && it + X_AHEAD < 10) {
#pragma unroll 1
            for (int k = it == 3 ? 4 : it + X_AHEAD; k <= it + X_AHEAD; k++) {
              mbar_expect_tx(bars + XFULL + k * 8, SLOT);
              tma4d(sb + k * SLOT, &maps.x, k * 64, 0, m * 4, 0, bars + XFULL + k * 8);
            }
          }
        }
        __syncwarp();
        if (++kb == 10) { kb = 0; j++; }
      }
      }
      uint32_t ep = 0;
      if (warp == 11 && lane == 0) {
        asm volatile("atom.relaxed.gpu.global.add.u32 %0, [%1], 1;" : "=r"(ep) : "l"(&g_ticket) : "memory");
        if (is_y) { prefetch_map(&maps.ht); prefetch_map(&maps.cre0); prefetch_map(&maps.cre1); prefetch_map(&maps.cim0); prefetch_map(&maps.cim1); }
        else { prefetch_map(&maps.h); prefetch_map(&maps.wd); prefetch_map(&maps.out); }
        sts_release(bars + EPOCH, ep / NCTA + 1u);
      }
      __syncwarp();
      ep = smem_wait_bits(bars + EPOCH, 0xffffffffu);
      if (warp == 9 || warp == 10) {
        const int wg = warp - 9;
        {
          const int rho = role * 16 + wg * 8 + (lane >> 2);
          const uint4* row = reinterpret_cast<const uint4*>(smem_raw + rho * 128) + ((lane & 3) ^ ((lane & 4)));
          float s0 = 0.f, s1 = 0.f, q0 = 0.f, q1 = 0.f;
#pragma unroll 1
          for (int kb = 0; kb < 10; kb++, row += SLOT / 16) {
            mbar_wait(bars + XFULL + kb * 8, 0);
            const uint4 v = row[0], u = row[(lane & 4) ? -4 : 4];
            const uint32_t w[8] = {v.x, v.y, v.z, v.w, u.x, u.y, u.z, u.w};
#pragma unroll
            for (int k = 0; k < 8; k++) { const float a = bf_lo(w[k]), c = bf_hi(w[k]); s0 += a; s1 += c; q0 = fmaf(a, a, q0); q1 = fmaf(c, c, q1); }
          }
          s0 += s1; q0 += q1;
#pragma unroll
          for (int o = 1; o < 4; o <<= 1) { s0 += __shfl_xor_sync(0xffffffffu, s0, o); q0 += __shfl_xor_sync(0xffffffffu, q0, o); }
          const float mean = s0 * (1.0f / D_);
          float den;
          asm("sqrt.approx.f32 %0, %1;" : "=f"(den) : "f"(round_bf(round_bf(fmaxf(fmaf(-mean, mean, q0 * (1.0f / D_)), 0.f)) + 1e-5f)));
          if ((lane & 3) == 0) st_tagged(&g_stat[m * 128 + rho], __uint_as_float(pack_bf16(mean, den)), ep);
          __syncwarp();
          if (wg == 0) TSTAMP_L0(1);
        }
        int j = wg ^ 1;
#pragma unroll 1
        while (j < njobs) {
          const int b = job_block(j, role);
          const uint2* src = g_cs + b * 128 + lane * 4;
          const uint2* src2 = g_stat + m * 128 + lane * 4;
          uint4 v0 = make_uint4(0u, ~ep, 0u, 0u), v1 = v0, v2 = make_uint4(0u, j < 2 ? ~ep : ep, 0u, ep), v3 = make_uint4(0u, ep, 0u, ep);
          const uint32_t t0 = clock32();
          while (true) {
            const bool m0 = ((v0.y ^ ep) | (v0.w ^ ep) | (v1.y ^ ep) | (v1.w ^ ep)) != 0, m1 = ((v2.y ^ ep) | (v2.w ^ ep) | (v3.y ^ ep) | (v3.w ^ ep)) != 0;
            if (m0) { v0 = ld_relaxed128(src); v1 = ld_relaxed128(src + 2); }
            if (m1) { v2 = ld_relaxed128(src2); v3 = ld_relaxed128(src2 + 2); }
            if (!__any_sync(0xffffffffu, m0 || m1) || clock32() - t0 > 1000000000u) break;
          }
          if (j < 2) {
            float4* dst = reinterpret_cast<float4*>(smem_raw + STAT_OFF) + lane * 2;
            dst[0] = make_float4(-bf_lo(v2.x), rcp(bf_hi(v2.x)), -bf_lo(v2.z), rcp(bf_hi(v2.z)));
            dst[1] = make_float4(-bf_lo(v3.x), rcp(bf_hi(v3.x)), -bf_lo(v3.z), rcp(bf_hi(v3.z)));
          }
          reinterpret_cast<uint4*>(smem_raw + CS_OFF + wg * 512)[lane] = make_uint4(v0.x, v0.z, v1.x, v1.z);
          TSTAMP_L0(57 + j);
          bar_arrive(NB_CS + wg, 160);
          bar_sync(NB_FLAG + wg, 160);
          fence_proxy_async();
          if (lane == 0) {
            if (b < 10) red_release_add(&g_flag[m * 32 + (b < 8 ? 27 : 30)], 1u);
            else st_release(&g_flag[m * 32 + b - 10], ep);
          }
          __syncwarp();
          j += 2;
        }
      } else {
        const uint32_t target = ep * (lane < 27 ? 1u : lane == 27 ? 8u : 2u);
        const uint32_t all = is_y ? 0x48000000u : 0x0fffffffu;
        const uint32_t need = warp == 8 ? all : is_y ? 0x08000000u : 0x08003fffu;
        uint32_t ready = 0;
        const uint32_t t0 = clock32();
        while ((ready & need) != need) {
          const uint32_t now = __ballot_sync(0xffffffffu, ld_relaxed(&g_flag[m * 32 + lane]) == target || clock32() - t0 > 1000000000u) & all;
          if (now != ready) {
            ready = now;
            asm volatile("fence.acquire.gpu;" ::: "memory");
            fence_proxy_async();
            if (warp == 8) sts_release(bars + READY, ready);
          } else {
            __nanosleep(200);
          }
        }
        if (warp == 11) {
      if (is_y) {
        const int d0 = role * YN0, half = role == 2 ? YN2 / 2 : YN0 / 2;
        int s = 0; uint32_t ph = 0;
#pragma unroll 1
        for (int kk = YS; kk < 20; kk++) {
          mbar_wait(bars + PEMPTY + s * 8, ph);
          if (kk == 16 && !(ready >> 30)) { smem_wait_bits(bars + READY, 1u << 30); fence_proxy_async(); }
          if (elect_one()) {
            const uint32_t dst = sb + s * Y_STAGE, fb = bars + PFULL + s * 8;
            const bool im = kk & 1;
            const int kc = (kk >> 1) * 64;
            mbar_expect_tx(fb, SLOT + half * 256);
            TRACE1(kk * 4 + 2);
            tma3d(dst, &maps.ht, 0, kc + (im ? P_ : 0), m * 2, fb);
            const CUtensorMap* mc = role == 2 ? (im ? &maps.cim0 : &maps.cre0) : (im ? &maps.cim1 : &maps.cre1);
            tma2d_mc(dst + SLOT + rank * half * 128, mc, kc, d0 + rank * half, fb);
          }
          __syncwarp();
          if (++s == Y_STAGES) { s = 0; ph ^= 1; }
        }
      } else {
        const int n0 = (role - 3) * 128;
        int s = 0; uint32_t ph = 0;
#pragma unroll 1
        for (int kk = 0; kk < 27; kk++) {
          if (YS && kk == 27 - O_LEAD) {
#pragma unroll 1
            for (int t = 0; t < YS; t++) {
              mbar_wait(bars + PEMPTY + s * 8, ph);
              if (elect_one()) {
                const uint32_t dst = sb + s * O_STAGE, fb = bars + PFULL + s * 8;
                mbar_expect_tx(fb, O_STAGE);
                tma3d(dst, &maps.ht, 0, (t >> 1) * 64 + (t & 1) * P_, m * 2, fb);
                tma2d_mc(dst + SLOT + rank * 8192, (t & 1) ? &maps.cim2 : &maps.cre2, (t >> 1) * 64, n0 + rank * 64, fb);
              }
              __syncwarp();
              if (++s == O_STAGES) { s = 0; ph ^= 1; }
            }
          }
          mbar_wait(bars + PEMPTY + s * 8, ph);
          const uint32_t bit = 1u << kk;
          if (!(ready & bit)) {
            ready |= __shfl_sync(0xffffffffu, smem_wait_bits(bars + READY, bit), 0);
            fence_proxy_async();
          }
          if (elect_one()) {
            const uint32_t dst = sb + s * O_STAGE, fb = bars + PFULL + s * 8;
            TRACE1(kk * 4 + 2);
            mbar_expect_tx(fb, O_STAGE);
            tma2d(dst, &maps.h, kk * 64, m * 128, fb);
            tma5d_mc(dst + SLOT + rank * 8192, &maps.wd, n0 + rank * 64, kk * 2, fb);
          }
          __syncwarp();
          if (++s == O_STAGES) { s = 0; ph ^= 1; }
        }
      }
        }
      }
    }
    cluster_sync_relaxed();
  } else {
    reg_alloc<232>();
    const int wg = warp >> 2;
    const int w4 = warp & 3;
    const int q = lane & 3, r8 = lane >> 2;
    const float2* s_stat = reinterpret_cast<const float2*>(smem_raw + STAT_OFF);
    float* s_cs = reinterpret_cast<float*>(smem_raw + CS_OFF + wg * 512);

    if (spare) {
      const uint32_t ep = smem_wait_bits(bars + EPOCH, 0xffffffffu);
      int s = 0; uint32_t ph = 0;
#pragma unroll 1
      for (int u = spare_id; u < 27; u += NSPARE) {
        float cs[4];
        zero_regs(cs);
#pragma unroll 1
        for (int kb = 0; kb < 5; kb++) {
          mbar_wait(bars + PFULL + s * 8, ph);
          const uint32_t ad = (SB >> 4) + s * (O_STAGE >> 4) + wg * 1024;
          wgmma_fence();
#pragma unroll
          for (int k = 0; k < 8; k++) WgmmaSS<8, 1, 0>::mma(cs, mkdesc(ad + DMN + k * 128), (uint64_t)((SB + ONES_OFF) >> 4), 1);
          wgmma_commit();
          wgmma_wait<0>();
          if ((threadIdx.x & 127) < CLUSTER) mbar_arrive(bars + PEMPTY + s * 8);
          if (++s == S_STAGES) { s = 0; ph ^= 1; }
        }
        fence_regs(cs);
        if (q < 2) st_tagged(&g_cs[(10 + u) * 128 + wg * 64 + w4 * 16 + q * 8 + r8], q ? cs[2] : cs[0], ep);
        TSTAMP_WG(8 + (u >> 2));
      }
      cluster_sync_relaxed();
      return;
    }
    const bool rel = (threadIdx.x & 127) < CLUSTER;
    uint32_t rbars;
    asm volatile("mapa.shared::cluster.u32 %0, %1, %2;" : "=r"(rbars) : "r"(bars), "r"(threadIdx.x & 1));

    const int lane_rel = (threadIdx.x & 127) / CLUSTER;
    const uint32_t prel = rbars + PEMPTY + (lane_rel & 7) * 8;

    const int slab = wg * 4 + w4;
    const int c0 = is_y ? role * YN0 : (role - 3) * 128;
    uint32_t xr[2][16];
#pragma unroll
    for (int i = 0; i < 16; i++) { xr[0][i] = 0; xr[1][i] = 0; }

    uint4* kcp = g_kc + (role * 16 + m) * 7 * 128 + (threadIdx.x & 127);

    float acc[2][64];
    auto mma_half = [&](auto isb_tag, uint32_t xd, uint32_t wd, int k0, bool accum) {
      constexpr bool ISB = decltype(isb_tag)::value;
#pragma unroll
      for (int k = k0; k < k0 + 2; k++) {
        if constexpr (ISB) {
          WgmmaSS<128, 0, 0>::mma(acc[0], mkdesc(wd + k * 2), mkdesc(xd + k * 2), accum || k);
          WgmmaSS<128, 0, 0>::mma(acc[1], mkdesc(wd + 512 + k * 2), mkdesc(xd + k * 2), accum || k);
        } else {
          WgmmaSS<128, 0, 1>::mma(acc[0], mkdesc(xd + k * 2), mkdesc(wd + k * 128), accum || k);
          WgmmaSS<128, 0, 1>::mma(acc[1], mkdesc(xd + 512 + k * 2), mkdesc(wd + k * 128), accum || k);
        }
      }
    };
    auto mainloop = [&](auto isb_tag, int j) {
      constexpr bool ISB = decltype(isb_tag)::value;
      constexpr uint32_t XD0 = (SB >> 4) + DK, WD0 = ((SB + WRING_OFF) >> 4) + (ISB ? DK : DMN);
      constexpr uint32_t WD_X = 0x1800, F_X = 0x30, E_X = 0xf0;
      static_assert(YS >= 1 && O_LEAD <= 5 && Y_LEAD <= 4, "the streamed segment must release every stage that is refilled");
      static_assert((WD0 ^ WD_X) == WD0 + 2048 && ((WD0 + 1024) ^ WD_X) == WD0 + 3072, "ring layout");
      static_assert((WFULL ^ F_X) == WFULL + 16 && ((WFULL + 8) ^ F_X) == WFULL + 24 && (WEMPTY ^ E_X) == WEMPTY + 16 && ((WEMPTY + 8) ^ E_X) == WEMPTY + 24, "barrier layout");
      const int s0 = (j & 1) * 2;
      uint32_t wd = WD0 + s0 * 1024, fb = bars + WFULL + s0 * 8, eb = rbars + WEMPTY + s0 * 8;
      uint32_t xd = XD0;
      {
        uint32_t pair = j * 5;
        int trig = (j == njobs - 1 && lane_rel < (is_y ? 2 : 4)) ? lane_rel + (is_y ? 2 : 1) : -1;
        asm volatile("" : "+r"(wd), "+r"(fb), "+r"(eb), "+r"(pair), "+r"(trig));
        peek_clear();
        if (!ISB || j > 0) bar_sync(NB_ORDER + wg, 256);
        TSTAMP_WG(8 + j * 4);
#pragma unroll 1
        for (int i = 0; i < 5; i++) {
          const uint32_t par = (pair >> 1) & 1;
          pair++;
          if (ISB) mbar_wait(bars + XFULL + i * 16, 0);
          wait_peeked(fb, par);
          TRACE(128 + j * 10 + 2 * i);
          wgmma_fence();
          mma_half(isb_tag, xd, wd, 0, i != 0);
          wgmma_commit();
          wgmma_wait<1>();
          arrive_if(rel && i != 0, (eb ^ E_X) + 8);
          peek(fb + 8, par);
          arrive_if(i == trig, prel);
          mma_half(isb_tag, xd, wd, 2, true);
          wgmma_commit();
          if (ISB) mbar_wait(bars + XFULL + i * 16 + 8, 0);
          wait_peeked(fb + 8, par);
          TRACE(128 + j * 10 + 2 * i + 1);
          wgmma_fence();
          mma_half(isb_tag, xd + 1024, wd + 1024, 0, true);
          wgmma_commit();
          wgmma_wait<1>();
          arrive_if(rel, eb);
          fb ^= F_X; eb ^= E_X;
          peek(fb, (pair >> 1) & 1);
          mma_half(isb_tag, xd + 1024, wd + 1024, 2, true);
          wgmma_commit();
          xd += 2048; wd ^= WD_X;
        }
        bar_arrive_if(j != njobs - 1, NB_ORDER + (wg ^ 1));
        if (ISB && j == 0) {
          bar_sync(NB_LEAD, 256);
          asm volatile("ld.shared.v4.u32 {%0,%1,%2,%3}, [%4];" : "=r"(xr[0][0]), "=r"(xr[1][0]), "=r"(xr[0][1]), "=r"(xr[1][1]) : "r"(sb + LAM_OFF + (w4 * 8 + r8) * 16) : "memory");
#pragma unroll
          for (int t = 1; t < 7; t++)
            asm volatile("ld.global.v4.u32 {%0,%1,%2,%3}, [%4];" : "=r"(xr[0][2 * t]), "=r"(xr[1][2 * t]), "=r"(xr[0][2 * t + 1]), "=r"(xr[1][2 * t + 1]) : "l"(kcp + t * 128) : "memory");
        }
        wgmma_wait<0>();
        arrive_if(rel, (eb ^ E_X) + 8);
        if (!ISB && (j & 2) && !is_y) {
          int ln = lane;
          asm volatile("" : "+r"(ln));
          const int rho = (ln & 1) + 4 * (slab & 1) + ((ln >> 2) & 2) + 8 * (4 * (slab >> 1) + ((ln >> 1) & 3));
          const uint32_t base = sb + (role - 3) * 2 * SLOT + rho * 128, sw = ((ln >> 4) ^ (rho & 7) ^ (ln & 6)) << 4;
#pragma unroll
          for (int jj = 0; jj < 16; jj += 2)
            ldsm4(xr[0][jj], xr[1][jj], xr[0][jj + 1], xr[1][jj + 1], base + (jj >> 3) * SLOT + (sw ^ ((jj & 7) << 4)));
          if (j == 3) bar_sync(NB_WG0, 128);
        }
        arrive_if(j >= njobs - 2 && trig < 0 && lane_rel < (is_y ? Y_STAGES : O_STAGES), prel);
      }
      fence_regs(acc[0]); fence_regs(acc[1]);
      TSTAMP_WG(8 + j * 4 + 1);
    };

    if (wg == 0) {
      const int idx = role * 16 + m, r = w4 * 4 + (lane >> 3), rb = min(r, 9);
      const uint4* srcb = reinterpret_cast<const uint4*>(idx < 64 ? ptrs.bre + (size_t)(idx * 10 + rb) * D_ : ptrs.bim + (size_t)((idx - 64) * 10 + rb) * D_) + (lane & 7);
      const int p = min((role + (lane >> 4) * 8) * 64 + w4 * 16 + (lane & 15), P_ - 1);
      const float par0 = __bfloat162float(ptrs.lam_re[p]), par1 = __bfloat162float(ptrs.lam_im[p]), par2 = __bfloat162float(ptrs.log_dt[p]);
      if (w4 < 3) {
        uint4 u[10];
#pragma unroll
        for (int i = 0; i < 10; i++) u[i] = __ldg(srcb + i * 8);
        float b0 = 0.f, b1 = 0.f;
#pragma unroll
        for (int i = 0; i < 10; i++) {
          b0 += (bf_lo(u[i].x) + bf_lo(u[i].y)) + (bf_lo(u[i].z) + bf_lo(u[i].w));
          b1 += (bf_hi(u[i].x) + bf_hi(u[i].y)) + (bf_hi(u[i].z) + bf_hi(u[i].w));
        }
        b0 += b1;
#pragma unroll
        for (int o = 4; o; o >>= 1) b0 += __shfl_xor_sync(0xffffffffu, b0, o);
        const uint32_t ep = smem_wait_bits(bars + EPOCH, 0xffffffffu);
        const int st = (idx & 63) * 10 + r;
        if ((lane & 7) == 0 && r < 10) st_tagged(&g_cs[(st >> 6) * 128 + (idx < 64 ? 0 : 64) + (st & 63)], b0, ep);
      }
      cplx lam, cf;
      ssm_params(par0, par1, par2, lam, cf);
#pragma unroll 1
      for (int pass = 0; pass < (role < 2 ? 4 : 2); pass++) {
        const int src = r8 + 8 * (pass ^ 1);
        const cplx l1 = cshfl(lam, src), c1 = cshfl(cf, src), zero = {0.f, 0.f}, one = {1.f, 0.f};
        cplx l32 = l1;
#pragma unroll
        for (int t = 0; t < 5; t++) l32 = cmul(l32, l32);
        const cplx l64 = cmul(l32, l32), l128 = cmul(l64, l64), l256 = cmul(l128, l128);
        const cplx k[7] = {l1, c1, csel(q >= 1, l32, zero), csel(q >= 2, l64, zero), cmul(l256, l256),
                           cmul(csel(q & 1, l128, one), csel(q & 2, l256, one)), cmul(c1, cmul(csel(q & 1, l32, one), csel(q & 2, l64, one)))};
#pragma unroll
        for (int t = 0; t < 7; t++) {
          xr[1][2 * t] = xr[0][2 * t]; xr[1][2 * t + 1] = xr[0][2 * t + 1];
          xr[0][2 * t] = __float_as_uint(k[t].r); xr[0][2 * t + 1] = __float_as_uint(k[t].i);
        }
        if (pass == 1) {
#pragma unroll
          for (int t = 1; t < 7; t++) stg128(kcp + t * 128, xr[0][2 * t], xr[1][2 * t], xr[0][2 * t + 1], xr[1][2 * t + 1]);
          if (q == 0) *reinterpret_cast<uint4*>(smem_raw + LAM_OFF + (w4 * 8 + r8) * 16) = make_uint4(xr[0][0], xr[1][0], xr[0][1], xr[1][1]);
          bar_arrive(NB_LEAD, 256);
          TSTAMP_WG(2);
        }
      }
    }

#pragma unroll 1
    for (int j = wg ^ 1; j < njobs; j += 2) {
    const int b = job_block(j, role);
    if (j == 1) {
#pragma unroll 1
      for (int k = 0; k < 10; k++) mbar_wait(bars + XFULL + k * 8, 0);
    }
    if (b < 10) {
      mainloop(BoolTag<true>{}, j);
      auto kc = [&](int h, int i) { return cplx{__uint_as_float(xr[h][2 * i]), __uint_as_float(xr[h][2 * i + 1])}; };
      cplx lamA = kc(0, 0), lamB = kc(1, 0);
      bar_sync(NB_CS + wg, 160);
      const uint32_t ep = lds_volatile(bars + EPOCH);
      const int pA = b * 64 + w4 * 16 + r8;
      const cplx csA = {s_cs[w4 * 16 + r8], s_cs[64 + w4 * 16 + r8]}, csB = {s_cs[w4 * 16 + r8 + 8], s_cs[64 + w4 * 16 + r8 + 8]};
      cplx aA = {0.f, 0.f}, aB = {0.f, 0.f};
#pragma unroll
      for (int i = 0; i < 16; i++) {
        const float4 st = *reinterpret_cast<const float4*>(s_stat + 8 * i + 2 * q);
#pragma unroll
        for (int e = 0; e < 2; e++) {
          float mb = e ? st.z : st.x;
          const float rd = e ? st.w : st.y;
          if ((YB & 1) || ((YB & 8) && e == 0)) yield_slot(ptrs.zero, ptrs.zero, __float_as_uint(aA.r), mb, aB.r);
          const int ia = 4 * i + e, ib = ia + 2;
          acc[0][ia] = fmaf(mb, csA.r, acc[0][ia]) * rd; acc[1][ia] = fmaf(mb, csA.i, acc[1][ia]) * rd;
          acc[0][ib] = fmaf(mb, csB.r, acc[0][ib]) * rd; acc[1][ib] = fmaf(mb, csB.i, acc[1][ib]) * rd;
          aA = cfma(lamA, aA, cplx{acc[0][ia], acc[1][ia]});
          aB = cfma(lamB, aB, cplx{acc[0][ib], acc[1][ib]});
        }
      }
      aA = cfma(kc(0, 2), cshfl(aA, lane - 1), aA); aB = cfma(kc(1, 2), cshfl(aB, lane - 1), aB);
      aA = cfma(kc(0, 3), cshfl(aA, lane - 2), aA); aB = cfma(kc(1, 3), cshfl(aB, lane - 2), aB);
      if (q == 3 && m < 15) {
        const uint64_t tg = (uint64_t)ep << 32;
        asm volatile("st.relaxed.gpu.global.v2.u64 [%0], {%1, %2};" :: "l"(&g_agg[m * P_ + pA]), "l"(tg | __float_as_uint(aA.r)), "l"(tg | __float_as_uint(aA.i)) : "memory");
        asm volatile("st.relaxed.gpu.global.v2.u64 [%0], {%1, %2};" :: "l"(&g_agg[m * P_ + pA + 8]), "l"(tg | __float_as_uint(aB.r)), "l"(tg | __float_as_uint(aB.i)) : "memory");
      }
      cplx eA = csel(q, cshfl(aA, lane - 1), cplx{0.f, 0.f}), eB = csel(q, cshfl(aB, lane - 1), cplx{0.f, 0.f});
      TSTAMP_WG(6 + j);
      cplx cfA = kc(0, 1), cfB = kc(1, 1);
      yield_slot(ptrs.zero, ptrs.zero, __float_as_uint(eA.r), cfA.i, cfB.i);
      eA = cmulc(cfA, eA); eB = cmulc(cfB, eB);
#pragma unroll
      for (int i = 0; i < 16; i++) {
#pragma unroll
        for (int e = 0; e < 2; e++) {
          const cplx ta = cmulc(cfA, cplx{acc[0][4 * i + e], acc[1][4 * i + e]});
          const cplx tb = cmulc(cfB, cplx{acc[0][4 * i + 2 + e], acc[1][4 * i + 2 + e]});
          acc[0][4 * i + e] = ta.r; acc[1][4 * i + e] = ta.i; acc[0][4 * i + 2 + e] = tb.r; acc[1][4 * i + 2 + e] = tb.i;
        }
        if (YB & 2) yield_slot(ptrs.zero, ptrs.zero, __float_as_uint(acc[1][4 * i + 3]), cfA.i, cfB.i);
      }
      cplx gA = {0.f, 0.f}, gB = {0.f, 0.f};
      {
        uint4 vA[4], vB[4];
        const uint4* ap = &g_agg[(m - 1 - q) * P_ + pA];
#pragma unroll
        for (int t = 0; t < 4; t++) { const uint32_t tg = m - 1 - q - 4 * t >= 0 ? ~ep : ep; vA[t] = make_uint4(0u, tg, 0u, ep); vB[t] = make_uint4(0u, ep, 0u, ep); }
        const uint32_t t0 = clock32();
        while (true) {
          bool miss = false;
#pragma unroll
          for (int t = 0; t < 4; t++) {
            const bool mt = ((vA[t].y ^ ep) | (vA[t].w ^ ep) | (vB[t].y ^ ep) | (vB[t].w ^ ep)) != 0;
            if (mt) { vA[t] = ld_relaxed128(ap - 4 * t * P_); vB[t] = ld_relaxed128(ap - 4 * t * P_ + 8); }
            miss |= mt;
          }
          if (!__any_sync(0xffffffffu, miss) || clock32() - t0 > 1000000000u) break;
        }
#pragma unroll
        for (int t = 3; t >= 0; t--) {
          gA = cfma(kc(0, 4), gA, cplx{__uint_as_float(vA[t].x), __uint_as_float(vA[t].z)});
          gB = cfma(kc(1, 4), gB, cplx{__uint_as_float(vB[t].x), __uint_as_float(vB[t].z)});
        }
      }
      gA = cmul(gA, kc(0, 5)); gB = cmul(gB, kc(1, 5));
#pragma unroll
      for (int o = 1; o < 4; o <<= 1) {
        gA.r += __shfl_xor_sync(0xffffffffu, gA.r, o); gA.i += __shfl_xor_sync(0xffffffffu, gA.i, o);
        gB.r += __shfl_xor_sync(0xffffffffu, gB.r, o); gB.i += __shfl_xor_sync(0xffffffffu, gB.i, o);
      }
      gA = cmulc(gA, kc(0, 6)); gB = cmulc(gB, kc(1, 6));
      gA.r += eA.r; gA.i += eA.i; gB.r += eB.r; gB.i += eB.i;
      lamA.i = -lamA.i; lamB.i = -lamB.i;
      TSTAMP_WG(8 + j * 4 + 2);
      __nv_bfloat16* hp = g_hT + (size_t)pA * L_ + m * 128 + q * 8;
#pragma unroll
      for (int c = 0; c < 4; c++) {
        uint32_t oAr[4], oAi[4], oBr[4], oBi[4];
#pragma unroll
        for (int ii = 0; ii < 4; ii++) {
          const int i = c * 4 + ii;
          const cplx a0 = cfma(lamA, gA, cplx{acc[0][4 * i], acc[1][4 * i]});
          const cplx b0 = cfma(lamB, gB, cplx{acc[0][4 * i + 2], acc[1][4 * i + 2]});
          gA = cfma(lamA, a0, cplx{acc[0][4 * i + 1], acc[1][4 * i + 1]});
          gB = cfma(lamB, b0, cplx{acc[0][4 * i + 3], acc[1][4 * i + 3]});
          oAr[ii] = pack_bf16(a0.r, gA.r); oAi[ii] = pack_bf16(a0.i, gA.i);
          oBr[ii] = pack_bf16(b0.r, gB.r); oBi[ii] = pack_bf16(b0.i, gB.i);
          if (YB & 4) yield_slot(ptrs.zero, ptrs.zero, oBi[ii], gA.i, gB.i);
        }
        stg128(hp + c * 32, oAr[0], oAr[1], oAr[2], oAr[3]);
        stg128(hp + c * 32 + 8 * L_, oBr[0], oBr[1], oBr[2], oBr[3]);
        stg128(hp + c * 32 + P_ * L_, oAi[0], oAi[1], oAi[2], oAi[3]);
        stg128(hp + c * 32 + (P_ + 8) * L_, oBi[0], oBi[1], oBi[2], oBi[3]);
      }
    } else {
      mainloop(BoolTag<false>{}, j);
      const int ft = b - 10;
      __nv_bfloat16* hp = g_H + (size_t)(m * 128 + (w4 >> 1) * 32 + (r8 >> 1) * 8 + (w4 & 1) * 4 + (r8 & 1)) * F_ + ft * 64 + q * 8;
      bar_sync(NB_CS + wg, 160);
      TSTAMP_WG(8 + j * 4 + 2);
      const int nap = j == 3 ? (is_y ? ptrs.zero : NAP3) : NAP;
      float mb[4], k0[4], k1[4];
#pragma unroll
      for (int rr = 0; rr < 4; rr++) {
        const float2 st = s_stat[(rr >> 1) * 64 + w4 * 16 + (rr & 1) * 8 + r8];
        mb[rr] = st.x; k0[rr] = st.y * 0.7978845608028654f; k1[rr] = k0[rr] * 0.044715f * st.y * st.y;
      }
#pragma unroll
      for (int a = 0; a < 2; a++) {
        float2 cg[4], cu[4];
#pragma unroll
        for (int jj = 0; jj < 4; jj++) {
          cg[jj] = *reinterpret_cast<const float2*>(s_cs + (a * 4 + jj) * 8 + q * 2);
          cu[jj] = *reinterpret_cast<const float2*>(s_cs + 64 + (a * 4 + jj) * 8 + q * 2);
        }
#pragma unroll
        for (int rr = 0; rr < 4; rr++) {
          const int mi = rr >> 1, hf = rr & 1;
          uint32_t o[4];
#pragma unroll
          for (int jj = 0; jj < 4; jj++) {
            const int i0 = 4 * (a * 4 + jj) + hf * 2;
            const float g0 = fmaf(mb[rr], cg[jj].x, acc[mi][i0]), g1 = fmaf(mb[rr], cg[jj].y, acc[mi][i0 + 1]);
            const float w0 = g0 * fmaf(mb[rr], cu[jj].x, acc[mi][32 + i0]), w1 = g1 * fmaf(mb[rr], cu[jj].y, acc[mi][32 + i0 + 1]);
            const float t0 = tanh_fast(g0 * fmaf(g0 * g0, k1[rr], k0[rr])), t1 = tanh_fast(g1 * fmaf(g1 * g1, k1[rr], k0[rr]));
            o[jj] = pack_bf16(fmaf(w0, t0, w0), fmaf(w1, t1, w1));
            if (YU == 2 && jj == 1) yield_slot(nap, ptrs.zero, o[jj], mb[rr]);
          }
          stg128(hp + (mi * 64 + hf * 2) * F_ + a * 32, o[0], o[1], o[2], o[3]);
          if (YU >= 2 && a * 4 + rr < 7) yield_slot(nap, ptrs.zero, o[3], mb[(rr + 1) & 3]);
        }
      }
    }
    bar_arrive(NB_FLAG + wg, 160);
    TSTAMP_WG(8 + j * 4 + 3);
    }

    TSTAMP_WG(32 + wg * 4);
    TDECL;
    peek_clear();
    const uint32_t par = lds_volatile(bars + EPOCH) & 1u;
    if (is_y) {
      auto y_job = [&](auto yn_tag) {
      constexpr int YN = decltype(yn_tag)::value;
      float ya[YN / 2];
      zero_regs(ya);
      uint32_t off = 0, fb = bars + PFULL, eb = 0, ph = 0;
      const uint32_t ad0 = (SB >> 4) + wg * 512 + DMN;
#pragma unroll 1
      for (int seg = 0; seg < 2; seg++) {
        if (seg == 1 && wg == 1) bar_sync(NB_LEAD, 256);
        const bool relp = rel && seg == 0;
#pragma unroll 1
        for (int n = seg ? Y_LEAD : 20 - YS - Y_LEAD; n > 0; n--) {
          wait_peeked(fb, ph);
          TRACE(((seg ? 20 : 20 - Y_LEAD) - n) * 4 + wg);
          const uint32_t ad = ad0 + off, wd = ((SB + SLOT) >> 4) + DK + off;
          wgmma_fence();
          WgmmaSS<YN, 1, 0>::mma(ya, mkdesc(ad), mkdesc(wd), 1);
          WgmmaSS<YN, 1, 0>::mma(ya, mkdesc(ad + 128), mkdesc(wd + 2), 1);
          wgmma_commit();
          wgmma_wait<1>();
          arrive_if(relp && eb != 0, eb);
          eb = fb + (rbars - bars) + (PEMPTY - PFULL);
          off += Y_STAGE >> 4; fb += 8;
          if (off == Y_STAGES * (Y_STAGE >> 4)) { off = 0; fb = bars + PFULL; ph ^= 1; }
          peek(fb, ph);
          WgmmaSS<YN, 1, 0>::mma(ya, mkdesc(ad + 256), mkdesc(wd + 4), 1);
          WgmmaSS<YN, 1, 0>::mma(ya, mkdesc(ad + 384), mkdesc(wd + 6), 1);
          wgmma_commit();
        }
      }
      if (wg == 0) bar_arrive(NB_LEAD, 256);
      wgmma_wait<0>();
      fence_regs(ya);
      TSTAMP_WG(32 + wg * 4 + 1);
      TDUMP(48 + wg);
      uint4* sp = g_s + ((size_t)(m * 8 + slab) * 40 + (c0 >> 4)) * 32 + lane;
#pragma unroll
      for (int jj = 0; jj < YN / 16; jj++) {
        const uint32_t w0 = (pack_bf16(ya[8 * jj], ya[8 * jj + 1]) & ~1u) | par, w1 = pack_bf16(ya[8 * jj + 2], ya[8 * jj + 3]);
        const uint32_t w2 = (pack_bf16(ya[8 * jj + 4], ya[8 * jj + 5]) & ~1u) | par, w3 = pack_bf16(ya[8 * jj + 6], ya[8 * jj + 7]);
        asm volatile("st.relaxed.gpu.global.v2.u64 [%0], {%1, %2};" :: "l"(sp + jj * 32), "l"((uint64_t)w0 | ((uint64_t)w1 << 32)), "l"((uint64_t)w2 | ((uint64_t)w3 << 32)) : "memory");
      }
      };
      if (role == 2) y_job(IntTag<YN2>{}); else y_job(IntTag<YN0>{});
    } else {
      float (&oa)[64] = acc[0];
      uint32_t xd[2][16];
      float sc0 = 0.f, sc1 = 0.f;
      uint32_t off = 0, fb = bars + PFULL, eb = 0, ph = 0;
      const uint32_t ad0 = (SB >> 4) + wg * 512 + DK;
      auto advance = [&]() {
        off += O_STAGE >> 4; fb += 8;
        if (off == O_STAGES * (O_STAGE >> 4)) { off = 0; fb = bars + PFULL; ph ^= 1; }
      };
      auto own_step = [&]() {
        wait_peeked(fb, ph);
        const uint32_t ad = ad0 + off, wd = ((SB + SLOT) >> 4) + DMN + off;
        advance();
        wgmma_fence();
        WgmmaSS<128, 0, 1>::mma(oa, mkdesc(ad), mkdesc(wd), 1);
        peek(fb, ph);
        WgmmaSS<128, 0, 1>::mma(oa, mkdesc(ad + 2), mkdesc(wd + 128), 1);
        WgmmaSS<128, 0, 1>::mma(oa, mkdesc(ad + 4), mkdesc(wd + 256), 1);
        WgmmaSS<128, 0, 1>::mma(oa, mkdesc(ad + 6), mkdesc(wd + 384), 1);
        wgmma_commit();
      };
      float4* hand = reinterpret_cast<float4*>(smem_raw + O_STAGES * O_STAGE) + (threadIdx.x & 127);
      {
        uint32_t dk[16];
#pragma unroll
        for (int jj = 0; jj < 16; jj++) dk[jj] = ldg32(ptrs.dskip + c0 + jj * 8 + q * 2);
        const int rho0 = (r8 & 1) + 4 * (slab & 1) + 8 * (4 * (slab >> 1) + (r8 >> 1));
        const float2 st[2] = {s_stat[rho0], s_stat[rho0 + 2]};
        sc0 = 0.25f * st[0].y * st[0].y; sc1 = 0.25f * st[1].y * st[1].y;
#pragma unroll
        for (int g = 0; g < 4; g++) {
          const int h = g >> 1, b8 = (g & 1) * 8;
          asm volatile("nanosleep.u32 %8;" : "+r"(xr[h][b8]), "+r"(xr[h][b8 + 1]), "+r"(xr[h][b8 + 2]), "+r"(xr[h][b8 + 3]),
                       "+r"(xr[h][b8 + 4]), "+r"(xr[h][b8 + 5]), "+r"(xr[h][b8 + 6]), "+r"(xr[h][b8 + 7]) : "n"(NAPX));
#pragma unroll
          for (int bit = 2; bit <= 4; bit <<= 1)
#pragma unroll
            for (int jj = b8; jj < b8 + 8; jj++)
              if (!(jj & bit)) {
                const uint32_t lo = xr[h][jj], hi = xr[h][jj | bit];
                xr[h][jj] = (r8 & bit) ? hi : lo; xr[h][jj | bit] = (r8 & bit) ? lo : hi;
              }
          const uint32_t mb = pack_bf16(st[h].x, st[h].x), rh = pack_bf16(st[h].y, st[h].y);
          const float rl_ = st[h].y - bf_lo(rh);
          const uint32_t rl = pack_bf16(rl_, rl_);
#pragma unroll
          for (int jj = b8; jj < b8 + 8; jj++) {
            const uint32_t d = hadd2_bf(xr[h][jj], mb);
            xd[h][jj] = hmul2_bf(hfma2_bf(d, rh, hmul2_bf(d, rl)), dk[jj]);
          }
        }
      }
      TSTAMP_WG(40 + wg);
      if (wg == 0) {
        const bool rel2 = (threadIdx.x & 127) < 2 * CLUSTER;
#pragma unroll 1
        for (int n = 0; n < O_SOLO; n++) {
          wait_peeked(fb, ph);
          TRACE(n * 4);
          const uint32_t ad = ad0 + off, wd = ((SB + SLOT) >> 4) + DMN + off;
          const uint32_t eb_next = fb + (rbars - bars) + (PEMPTY - PFULL);
          advance();
          wgmma_fence();
          mma_half(BoolTag<false>{}, ad, wd, 0, n != 0);
          wgmma_commit();
          wgmma_wait<1>();
          arrive_if(rel2 && eb != 0, eb);
          peek(fb, ph);
          mma_half(BoolTag<false>{}, ad, wd, 2, true);
          wgmma_commit();
          eb = eb_next;
        }
        bar_arrive(NB_ORDER + 1, 256);
        wgmma_wait<0>();
        fence_regs(acc[0]); fence_regs(acc[1]);
        arrive_if(rel2, eb);
        eb = 0;
#pragma unroll
        for (int i = 0; i < 16; i++) hand[i * 128] = make_float4(acc[1][4 * i], acc[1][4 * i + 1], acc[1][4 * i + 2], acc[1][4 * i + 3]);
        bar_arrive(NB_HAND, 256);
      } else {
        off = (O_SOLO % O_STAGES) * (O_STAGE >> 4); fb += (O_SOLO % O_STAGES) * 8; ph = (O_SOLO / O_STAGES) & 1;
        zero_regs(oa);
        wgmma_fence();
        bar_sync(NB_ORDER + 1, 256);
      }
#pragma unroll
      for (int seg = 0; seg < 2; seg++) {
        if (seg == 1) {
          if (YS) {
            uint32_t ey[YS ? YS : 1];
#pragma unroll
            for (int t = 0; t < YS; t++) {
              wait_peeked(fb, ph);
              const uint32_t ad = (SB >> 4) + wg * 512 + DMN + off, wd = ((SB + SLOT) >> 4) + DK + off;
              ey[t] = fb + (rbars - bars) + (PEMPTY - PFULL);
              advance();
              wgmma_fence();
#pragma unroll
              for (int k = 0; k < 4; k++) WgmmaSS<128, 1, 0>::mma(acc[1], mkdesc(ad + k * 128), mkdesc(wd + k * 2), (t | k) != 0);
              peek(fb, ph);
              wgmma_commit();
            }
            wgmma_wait<0>();
            fence_regs(acc[0]); fence_regs(acc[1]);
            arrive_if(rel, eb);
#pragma unroll
            for (int t = 0; t < YS; t++) arrive_if(rel, ey[t]);
#pragma unroll
            for (int jj = 0; jj < 16; jj++) {
              xd[0][jj] = hadd2_bf(xd[0][jj], pack_bf16(acc[1][4 * jj], acc[1][4 * jj + 1]));
              xd[1][jj] = hadd2_bf(xd[1][jj], pack_bf16(acc[1][4 * jj + 2], acc[1][4 * jj + 3]));
            }
          }
          if (wg == 1) {
            bar_sync(NB_HAND, 256);
#pragma unroll
            for (int i = 0; i < 16; i++) { const float4 v = hand[i * 128]; oa[4 * i] += v.x; oa[4 * i + 1] += v.y; oa[4 * i + 2] += v.z; oa[4 * i + 3] += v.w; }
            bar_sync(NB_LEAD, 256);
          }
        }
        const bool relp = rel && seg == 0;
        int n = seg ? O_LEAD : 27 - O_LEAD - O_SOLO;
#pragma unroll 1
        do {
          const uint32_t eb_next = fb + (rbars - bars) + (PEMPTY - PFULL);
          TRACE(((seg ? 27 : 27 - O_LEAD) - n) * 4 + wg);
          own_step();
          wgmma_wait<1>();
          arrive_if(relp && eb != 0, eb);
          eb = eb_next;
        } while (--n);
      }
      if (wg == 0) bar_arrive(NB_LEAD, 256);
      const uint4* sp = g_s + ((size_t)(m * 8 + slab) * 40 + (role - 3) * 8) * 32 + lane;
      uint64_t sw[16];
#pragma unroll
      for (int jj = 0; jj < 8; jj++) asm volatile("ld.relaxed.gpu.global.v2.u64 {%0, %1}, [%2];" : "=l"(sw[2 * jj]), "=l"(sw[2 * jj + 1]) : "l"(sp + jj * 32) : "memory");
      wgmma_wait<0>();
      fence_regs(oa);
      TSTAMP_WG(32 + wg * 4 + 1);
      TDUMP(48 + wg);
#pragma unroll
      for (int i = 0; i < 16 * PRE_SILU; i++) {
        const float h = oa[i] * ((i & 2) ? sc1 : sc0);
        oa[i] = fmaf(h, tanh_fast(h), h);
      }
      {
        uint32_t bad = 0;
#pragma unroll
        for (int jj = 0; jj < 16; jj++) bad |= (uint32_t)sw[jj] ^ par;
        if (__any_sync(0xffffffffu, bad & 1u)) {
          const uint32_t t0 = clock32();
          const uint4* lp = sp + (role == 4 ? 4 : role == 6 ? 1 : 7) * 32;
          while (clock32() - t0 < 1000000000u) {
            uint32_t w0, w1;
            asm volatile("ld.relaxed.gpu.global.u32 %0, [%1];" : "=r"(w0) : "l"(lp) : "memory");
            asm volatile("ld.relaxed.gpu.global.u32 %0, [%1];" : "=r"(w1) : "l"(sp + 7 * 32) : "memory");
            if (!__any_sync(0xffffffffu, ((w0 ^ par) | (w1 ^ par)) & 1u)) break;
          }
          while (true) {
            bool miss = false;
#pragma unroll
            for (int jj = 0; jj < 8; jj++) {
              const bool mt = (((uint32_t)sw[2 * jj] ^ par) | ((uint32_t)sw[2 * jj + 1] ^ par)) & 1u;
              if (mt) asm volatile("ld.relaxed.gpu.global.v2.u64 {%0, %1}, [%2];" : "=l"(sw[2 * jj]), "=l"(sw[2 * jj + 1]) : "l"(sp + jj * 32) : "memory");
              miss |= mt;
            }
            if (!__any_sync(0xffffffffu, miss) || clock32() - t0 > 1000000000u) break;
          }
        }
      }
      TSTAMP_WG(32 + wg * 4 + 2);
      constexpr int T0 = 27 + YS - O_STAGES;
      if (wg == 0) mbar_wait(bars + PEMPTY + (T0 % O_STAGES) * 8, (T0 / O_STAGES + 1) & 1);
      uint8_t* buf = smem_raw + (wg ? O_STAGES : T0 % O_STAGES) * O_STAGE + w4 * 8192;
#pragma unroll
      for (int t = 0; t < 4; t++) {
        if (t + PRE_SILU < 4) {
#pragma unroll
          for (int i = 16 * (t + PRE_SILU); i < 16 * (t + PRE_SILU + 1); i++) {
            const float h = oa[i] * ((i & 2) ? sc1 : sc0);
            oa[i] = fmaf(h, tanh_fast(h), h);
          }
        }
#pragma unroll
        for (int j4 = 0; j4 < 4; j4++) {
          const int jj = t * 4 + j4;
          uint8_t* p = buf + t * 2048 + r8 * 128 + (((j4 * 2 + (q >> 1)) ^ r8) << 4) + (q & 1) * 8;
          const uint32_t s0 = hadd2_bf(xd[0][jj], (uint32_t)sw[jj]), s1 = hadd2_bf(xd[1][jj], (uint32_t)(sw[jj] >> 32));
          *reinterpret_cast<float2*>(p) = make_float2(fmaf(bf_lo(s0), oa[4 * jj], bf_lo(xr[0][jj])), fmaf(bf_hi(s0), oa[4 * jj + 1], bf_hi(xr[0][jj])));
          *reinterpret_cast<float2*>(p + 1024) = make_float2(fmaf(bf_lo(s1), oa[4 * jj + 2], bf_lo(xr[1][jj])), fmaf(bf_hi(s1), oa[4 * jj + 3], bf_hi(xr[1][jj])));
        }
        asm volatile("fence.proxy.async.shared::cta;" ::: "memory");
        __syncwarp();
        if (elect_one()) {
          asm volatile("cp.async.bulk.tensor.5d.global.shared::cta.bulk_group [%0, {%2, %2, %3, %4, %5}], [%1];"
            :: "l"(&maps.out), "r"(smem_u32(buf) + t * 2048), "r"(0), "r"(m * 4 + (slab & 1) * 2), "r"(slab >> 1), "r"((role - 3) * 4 + t) : "memory");
        }
      }
      asm volatile("cp.async.bulk.commit_group;" ::: "memory");
      asm volatile("cp.async.bulk.wait_group.read 0;" ::: "memory");
      __syncwarp();
    }
    TSTAMP_WG(32 + wg * 4 + 3);
    cluster_sync_relaxed();
  }
}

typedef CUresult (*EncodeFn)(CUtensorMap*, CUtensorMapDataType, cuuint32_t, void*, const cuuint64_t*, const cuuint64_t*,
                             const cuuint32_t*, const cuuint32_t*, CUtensorMapInterleave, CUtensorMapSwizzle,
                             CUtensorMapL2promotion, CUtensorMapFloatOOBfill);

bool encode(EncodeFn fn, CUtensorMap* m, const void* base, int rank, const uint64_t* dims, const uint64_t* strides, const uint32_t* box,
            CUtensorMapDataType dt = CU_TENSOR_MAP_DATA_TYPE_BFLOAT16) {
  cuuint64_t d[5], s[5]; cuuint32_t b[5], e[5];
  for (int i = 0; i < rank; i++) { d[i] = dims[i]; b[i] = box[i]; e[i] = 1; if (i + 1 < rank) s[i] = strides[i]; }
  CUresult r = fn(m, dt, rank, const_cast<void*>(base), d, s, b, e, CU_TENSOR_MAP_INTERLEAVE_NONE,
                  CU_TENSOR_MAP_SWIZZLE_128B, CU_TENSOR_MAP_L2_PROMOTION_L2_256B, CU_TENSOR_MAP_FLOAT_OOB_FILL_NONE);
  if (r != CUDA_SUCCESS) { fprintf(stderr, "cuTensorMapEncodeTiled failed: %d\n", (int)r); return false; }
  return true;
}
bool encode2d(EncodeFn fn, CUtensorMap* m, const void* base, uint64_t inner, uint64_t outer, uint32_t box_outer) {
  const uint64_t dims[2] = {inner, outer}, str[1] = {inner * 2};
  const uint32_t box[2] = {64, box_outer};
  return encode(fn, m, base, 2, dims, str, box);
}

}

extern "C" void kernel_launch(void* const* d_in, const int* in_sizes, int n_in, void* d_out, int out_size) {
  (void)in_sizes; (void)n_in; (void)out_size;
  static EncodeFn fn = nullptr;
  if (!fn) {
    void* p = nullptr; cudaDriverEntryPointQueryResult st;
    if (cudaGetDriverEntryPoint("cuTensorMapEncodeTiled", &p, cudaEnableDefault, &st) != cudaSuccess || !p) { fprintf(stderr, "no cuTensorMapEncodeTiled\n"); return; }
    fn = (EncodeFn)p;
    cudaFuncSetAttribute(fused_kernel, cudaFuncAttributeMaxDynamicSharedMemorySize, SMEM_BYTES);
  }
  void *H, *hT;
  cudaGetSymbolAddress(&H, g_H); cudaGetSymbolAddress(&hT, g_hT);
  Maps maps;
  bool ok = true;
  {
    const uint64_t dims[4] = {D_, 2, L_ / 32, 16}, str[3] = {D_ * 2, 32 * D_ * 2, 2 * D_ * 2};
    const uint32_t box[4] = {64, 2, 4, 16};
    ok &= encode(fn, &maps.x, d_in[0], 4, dims, str, box);
  }
  ok &= encode2d(fn, &maps.bre, d_in[3], D_, P_, 64);
  ok &= encode2d(fn, &maps.bim, d_in[4], D_, P_, 64);
  ok &= encode2d(fn, &maps.wg, d_in[10], F_, D_, 64);
  ok &= encode2d(fn, &maps.wu, d_in[11], F_, D_, 64);
  ok &= encode2d(fn, &maps.h, H, F_, L_, 128);
  {
    const uint64_t dims[5] = {D_, 2, 4, 4, F_ / 32}, str[4] = {D_ * 2, 8 * D_ * 2, 2 * D_ * 2, 32 * D_ * 2};
    const uint32_t box[5] = {64, 2, 4, 4, 2};
    ok &= encode(fn, &maps.wd, d_in[12], 5, dims, str, box);
  }
  {
    const uint64_t dims[3] = {64, 2 * P_, L_ / 64}, str[2] = {L_ * 2, 128};
    const uint32_t box[3] = {64, 64, 2};
    ok &= encode(fn, &maps.ht, hT, 3, dims, str, box);
  }
  ok &= encode2d(fn, &maps.cre0, d_in[5], P_, D_, 112);
  ok &= encode2d(fn, &maps.cre1, d_in[5], P_, D_, 104);
  ok &= encode2d(fn, &maps.cim0, d_in[6], P_, D_, 112);
  ok &= encode2d(fn, &maps.cim1, d_in[6], P_, D_, 104);
  ok &= encode2d(fn, &maps.cre2, d_in[5], P_, D_, 64);
  ok &= encode2d(fn, &maps.cim2, d_in[6], P_, D_, 64);
  {
    const uint64_t dims[5] = {32, 8, L_ / 32, 4, D_ / 32}, str[4] = {D_ * 4, 32 * D_ * 4, 8 * D_ * 4, 128};
    const uint32_t box[5] = {32, 8, 2, 1, 1};
    ok &= encode(fn, &maps.out, d_out, 5, dims, str, box, CU_TENSOR_MAP_DATA_TYPE_FLOAT32);
  }
  if (!ok) return;

  cudaLaunchConfig_t cfg = {};
  cfg.gridDim = dim3(NCTA); cfg.blockDim = dim3(384); cfg.dynamicSmemBytes = SMEM_BYTES; cfg.stream = cudaStreamPerThread;
  cudaLaunchAttribute at[1];
  at[0].id = cudaLaunchAttributeClusterDimension; at[0].val.clusterDim.x = CLUSTER; at[0].val.clusterDim.y = 1; at[0].val.clusterDim.z = 1;
  cfg.attrs = at; cfg.numAttrs = CLUSTER > 1 ? 1 : 0;
  typedef const __nv_bfloat16* BP;
  const Ptrs ptrs = {(BP)d_in[0], (BP)d_in[1], (BP)d_in[2], (BP)d_in[7], (BP)d_in[8], (BP)d_in[3], (BP)d_in[4], (BP)d_in[5], (BP)d_in[6], (BP)d_in[12], 0};
  cudaLaunchKernelEx(&cfg, fused_kernel, maps, ptrs);
}
```

```cpp
#include <cuda_runtime.h>
#include <cuda_bf16.h>
#include <cuda.h>
#include <stdint.h>
#include <stdio.h>

constexpr int CLUSTER = 2;

namespace {

constexpr int L_ = 2048, D_ = 640, P_ = 640, F_ = 1728;
constexpr int NSPARE = 4;
constexpr int NCTA = 128 + NSPARE;
constexpr int SLOT = 16384;
constexpr int WRING_OFF = 10 * SLOT;
constexpr int BAR_OFF = 14 * SLOT;
constexpr int STAT_OFF = BAR_OFF + 256;
constexpr int CS_OFF = STAT_OFF + 1024;
constexpr int ONES_OFF = CS_OFF + 1024;
constexpr int SMEM_BYTES = ONES_OFF + 256;
constexpr uint32_t SB = 0x400;
constexpr int YN0 = 208, YN2 = 224;
constexpr int Y_STAGES = 5;
constexpr int O_STAGE = 2 * SLOT;
constexpr int O_STAGES = 6;
constexpr int S_STAGES = 6;
constexpr int NAP = 64;
constexpr int O_SOLO = 11;
constexpr int YS = 1;
constexpr int NAPX = 32;
constexpr int NAP3 = 32;
constexpr int S_AT = 2;
constexpr int NAP0 = 16;
constexpr int NAPS = 64;
constexpr int Y_LEAD = 4;
constexpr int O_LEAD = 5;

__device__ __align__(1024) uint4 g_H[16 * 27 * 1024];
__device__ __align__(1024) uint4 g_hT[16 * 20 * 1024];
__device__ __align__(1024) uint4 g_s[L_ * D_ / 8];
__device__ __align__(256) uint4 g_agg[16 * P_];
__device__ __align__(256) uint2 g_cs[37 * 128];
__device__ __align__(256) uint2 g_stat[L_];
__device__ __align__(256) uint4 g_kc[32 * 7 * 128];
__device__ __align__(256) uint32_t g_ticket;
__device__ __align__(256) uint32_t g_flag[16 * 32];

struct Maps {
  CUtensorMap x, bre, bim, wg, wu, wd, cre0, cre1, cim0, cim1, cre2, cim2, out;
};

__device__ __forceinline__ uint32_t smem_u32(const void* p) { return (uint32_t)__cvta_generic_to_shared(p); }
__device__ __forceinline__ void mbar_init(uint32_t bar, uint32_t count) { asm volatile("mbarrier.init.shared::cta.b64 [%0], %1;" :: "r"(bar), "r"(count) : "memory"); }
__device__ __forceinline__ void mbar_expect_tx(uint32_t bar, uint32_t bytes) { asm volatile("mbarrier.arrive.expect_tx.shared::cta.b64 _, [%0], %1;" :: "r"(bar), "r"(bytes) : "memory"); }
__device__ __forceinline__ void mbar_arrive(uint32_t bar) { asm volatile("mbarrier.arrive.shared::cta.b64 _, [%0];" :: "r"(bar) : "memory"); }
__device__ __forceinline__ void mbar_wait(uint32_t bar, uint32_t parity) {
  asm volatile("{\n.reg .pred p;\n.reg .u32 t0, t1;\n"
    "mbarrier.try_wait.parity.shared::cta.b64 p, [%0], %1;\n@p bra LAB_DONE;\n"
    "mov.u32 t0, %%clock;\n"
    "LAB_WAIT:\n"
    "mbarrier.try_wait.parity.shared::cta.b64 p, [%0], %1;\n@p bra LAB_DONE;\n"
    "mov.u32 t1, %%clock;\nsub.u32 t1, t1, t0;\nsetp.gt.u32 p, t1, 1000000000;\n@p trap;\nbra LAB_WAIT;\n"
    "LAB_DONE:\n}" :: "r"(bar), "r"(parity) : "memory");
}
__device__ __forceinline__ uint32_t ld_relaxed(const uint32_t* p) { uint32_t v; asm volatile("ld.relaxed.gpu.global.u32 %0, [%1];" : "=r"(v) : "l"(p) : "memory"); return v; }
__device__ __forceinline__ void red_release_add(uint32_t* p, uint32_t v) { asm volatile("red.release.gpu.global.add.u32 [%0], %1;" :: "l"(p), "r"(v) : "memory"); }
__device__ __forceinline__ void st_release(uint32_t* p, uint32_t v) { asm volatile("st.release.gpu.global.u32 [%0], %1;" :: "l"(p), "r"(v) : "memory"); }
__device__ __forceinline__ void fence_proxy_async() { asm volatile("fence.proxy.async.global;" ::: "memory"); }
__device__ __forceinline__ void trap_if(bool c) { asm volatile("{\n.reg .pred p;\nsetp.ne.u32 p, %0, 0;\n@p trap;\n}" :: "r"((uint32_t)c)); }
__device__ __forceinline__ uint32_t clock32() { uint32_t c; asm volatile("mov.u32 %0, %%clock;" : "=r"(c) :: "memory"); return c; }

__device__ __forceinline__ bool elect_one() {
  uint32_t p;
  asm volatile("{\n.reg .pred P;\nelect.sync _|P, 0xffffffff;\nselp.u32 %0, 1, 0, P;\n}" : "=r"(p));
  return p;
}
__device__ __forceinline__ void tma2d(uint32_t dst, const CUtensorMap* map, int c0, int c1, uint32_t bar) {
  asm volatile("cp.async.bulk.tensor.2d.shared::cluster.global.mbarrier::complete_tx::bytes [%0], [%1, {%3, %4}], [%2];"
    :: "r"(dst), "l"(map), "r"(bar), "r"(c0), "r"(c1) : "memory");
}
__device__ __forceinline__ void tma2d_mc(uint32_t dst, const CUtensorMap* map, int c0, int c1, uint32_t bar) {
  asm volatile("cp.async.bulk.tensor.2d.shared::cluster.global.mbarrier::complete_tx::bytes.multicast::cluster [%0], [%1, {%3, %4}], [%2], %5;"
    :: "r"(dst), "l"(map), "r"(bar), "r"(c0), "r"(c1), "h"((uint16_t)3) : "memory");
}
__device__ __forceinline__ void tma4d(uint32_t dst, const CUtensorMap* map, int c0, int c1, int c2, int c3, uint32_t bar) {
  asm volatile("cp.async.bulk.tensor.4d.shared::cluster.global.mbarrier::complete_tx::bytes [%0], [%1, {%3, %4, %5, %6}], [%2];"
    :: "r"(dst), "l"(map), "r"(bar), "r"(c0), "r"(c1), "r"(c2), "r"(c3) : "memory");
}
__device__ __forceinline__ void tma5d_mc(uint32_t dst, const CUtensorMap* map, int c0, int c4, uint32_t bar) {
  asm volatile("cp.async.bulk.tensor.5d.shared::cluster.global.mbarrier::complete_tx::bytes.multicast::cluster [%0], [%1, {%3, %5, %5, %5, %4}], [%2], %6;"
    :: "r"(dst), "l"(map), "r"(bar), "r"(c0), "r"(c4), "r"(0), "h"((uint16_t)3) : "memory");
}
__device__ __forceinline__ void bulk_load(uint32_t dst, const void* src, uint32_t bytes, uint32_t bar) {
  asm volatile("cp.async.bulk.shared::cluster.global.mbarrier::complete_tx::bytes [%0], [%1], %2, [%3];" :: "r"(dst), "l"(src), "r"(bytes), "r"(bar) : "memory");
}
__device__ __forceinline__ void prefetch_l2(const void* p, uint32_t bytes) { asm volatile("cp.async.bulk.prefetch.L2.global [%0], %1;" :: "l"(p), "r"(bytes) : "memory"); }
__device__ __forceinline__ void prefetch_map(const CUtensorMap* map) { asm volatile("prefetch.tensormap [%0];" :: "l"(map) : "memory"); }
__device__ __forceinline__ void wgmma_fence() { asm volatile("wgmma.fence.sync.aligned;" ::: "memory"); }
__device__ __forceinline__ void wgmma_commit() { asm volatile("wgmma.commit_group.sync.aligned;" ::: "memory"); }
template<int N> __device__ __forceinline__ void wgmma_wait() { asm volatile("wgmma.wait_group.sync.aligned %0;" :: "n"(N) : "memory"); }
template<int N> __device__ __forceinline__ void zero_regs(float (&d)[N]) {
#pragma unroll
  for (int i = 0; i < N; i++) asm volatile("mov.b32 %0, 0;" : "=f"(d[i]));
}
template<int N> __device__ __forceinline__ void fence_regs(float (&d)[N]) {
#pragma unroll
  for (int i = 0; i < N; i++) asm volatile("" : "+f"(d[i]) :: "memory");
}
constexpr uint32_t DK = 1u << 16, DMN = 512u << 16;
__device__ __forceinline__ uint64_t mkdesc(uint32_t lo) { return (uint64_t)lo | ((uint64_t)0x40000040u << 32); }
constexpr uint32_t DMN64 = 256u << 16;
__device__ __forceinline__ uint64_t mkdesc64(uint32_t lo) { return (uint64_t)lo | ((uint64_t)0x80000020u << 32); }
__device__ __forceinline__ void arrive_if(bool p, uint32_t addr) {
  asm volatile("{\n.reg .pred p;\nsetp.ne.u32 p, %0, 0;\n@p mbarrier.arrive.shared::cluster.b64 _, [%1];\n}" :: "r"((uint32_t)p), "r"(addr) : "memory");
}
__device__ __forceinline__ void peek_clear() { asm volatile("setp.ne.u32 peekp, 0, 0;" ::: "memory"); }
__device__ __forceinline__ void peek(uint32_t bar, uint32_t parity) {
  asm volatile("mbarrier.test_wait.parity.shared::cta.b64 peekp, [%0], %1;" :: "r"(bar), "r"(parity) : "memory");
}
__device__ __forceinline__ void wait_peeked(uint32_t bar, uint32_t parity) {
  asm volatile("{\n.reg .pred p;\n.reg .u32 t0, t1;\n"
    "@peekp bra LAB_DONE;\n"
    "mov.u32 t0, %%clock;\n"
    "LAB_WAIT:\n"
    "mbarrier.try_wait.parity.shared::cta.b64 p, [%0], %1;\n@p bra LAB_DONE;\n"
    "mov.u32 t1, %%clock;\nsub.u32 t1, t1, t0;\nsetp.gt.u32 p, t1, 1000000000;\n@p trap;\nbra LAB_WAIT;\n"
    "LAB_DONE:\n}" :: "r"(bar), "r"(parity) : "memory");
}
__device__ __forceinline__ uint32_t lds_volatile(uint32_t addr) { uint32_t v; asm volatile("ld.acquire.cta.shared::cta.u32 %0, [%1];" : "=r"(v) : "r"(addr) : "memory"); return v; }
__device__ __forceinline__ void sts_release(uint32_t addr, uint32_t v) { asm volatile("st.release.cta.shared::cta.u32 [%0], %1;" :: "r"(addr), "r"(v) : "memory"); }
__device__ __forceinline__ uint32_t smem_wait_bits(uint32_t addr, uint32_t mask) {
  uint32_t v;
  asm volatile("{\n.reg .pred p;\n.reg .u32 t0, t1;\n"
    "mov.u32 t0, %%clock;\n"
    "LAB_WAIT:\n"
    "ld.acquire.cta.shared::cta.u32 %0, [%1];\nand.b32 t1, %0, %2;\nsetp.ne.u32 p, t1, 0;\n@p bra LAB_DONE;\n"
    "mov.u32 t1, %%clock;\nsub.u32 t1, t1, t0;\nsetp.gt.u32 p, t1, 1000000000;\n@p trap;\nbra LAB_WAIT;\n"
    "LAB_DONE:\n}" : "=r"(v) : "r"(addr), "r"(mask) : "memory");
  return v;
}
__device__ __forceinline__ void ldsm4(uint32_t& r0, uint32_t& r1, uint32_t& r2, uint32_t& r3, uint32_t addr) {
  asm volatile("ldmatrix.sync.aligned.m8n8.x4.shared.b16 {%0,%1,%2,%3}, [%4];" : "=r"(r0), "=r"(r1), "=r"(r2), "=r"(r3) : "r"(addr) : "memory");
}
__device__ __forceinline__ uint4 ld_relaxed128(const void* p) {
  uint64_t a, b;
  asm volatile("ld.relaxed.gpu.global.v2.u64 {%0, %1}, [%2];" : "=l"(a), "=l"(b) : "l"(p) : "memory");
  return make_uint4((uint32_t)a, (uint32_t)(a >> 32), (uint32_t)b, (uint32_t)(b >> 32));
}
__device__ __forceinline__ void st_tagged(void* p, float v, uint32_t tag) {
  asm volatile("st.relaxed.gpu.global.u64 [%0], %1;" :: "l"(p), "l"((uint64_t)__float_as_uint(v) | ((uint64_t)tag << 32)) : "memory");
}
__device__ __forceinline__ void cluster_sync_relaxed() {
  asm volatile("barrier.cluster.arrive.relaxed.aligned;\nbarrier.cluster.wait.aligned;" ::: "memory");
}
__device__ __forceinline__ void bar_sync(int id, int n) { asm volatile("bar.sync %0, %1;" :: "r"(id), "r"(n) : "memory"); }
__device__ __forceinline__ void bar_arrive(int id, int n) { asm volatile("bar.arrive %0, %1;" :: "r"(id), "r"(n) : "memory"); }
__device__ __forceinline__ void bar_arrive_if(bool p, int id) {
  asm volatile("{\n.reg .pred p;\nsetp.ne.u32 p, %0, 0;\n@p bar.arrive %1, 256;\n}" :: "r"((uint32_t)p), "r"(id) : "memory");
}
template<int R> __device__ __forceinline__ void reg_alloc() { asm volatile("setmaxnreg.inc.sync.aligned.u32 %0;" :: "n"(R)); }
template<int R> __device__ __forceinline__ void reg_dealloc() { asm volatile("setmaxnreg.dec.sync.aligned.u32 %0;" :: "n"(R)); }
__device__ __forceinline__ uint32_t pack_bf16(float lo, float hi) { uint32_t r; asm("cvt.rn.bf16x2.f32 %0, %1, %2;" : "=r"(r) : "f"(hi), "f"(lo)); return r; }
__device__ __forceinline__ float bf_lo(uint32_t v) { return __uint_as_float(v << 16); }
__device__ __forceinline__ float bf_hi(uint32_t v) { return __uint_as_float(v & 0xffff0000u); }
__device__ __forceinline__ float round_bf(float v) { return bf_lo(pack_bf16(v, 0.f)); }
__device__ __forceinline__ float ex2(float x) { float y; asm("ex2.approx.ftz.f32 %0, %1;" : "=f"(y) : "f"(x)); return y; }
__device__ __forceinline__ float rcp(float x) { float y; asm("rcp.approx.ftz.f32 %0, %1;" : "=f"(y) : "f"(x)); return y; }
__device__ __forceinline__ uint32_t hmul2_bf(uint32_t a, uint32_t b) { uint32_t r; asm("mul.rn.bf16x2 %0, %1, %2;" : "=r"(r) : "r"(a), "r"(b)); return r; }
__device__ __forceinline__ uint32_t hadd2_bf(uint32_t a, uint32_t b) { uint32_t r; asm("add.rn.bf16x2 %0, %1, %2;" : "=r"(r) : "r"(a), "r"(b)); return r; }
__device__ __forceinline__ uint32_t hfma2_bf(uint32_t a, uint32_t b, uint32_t c) { uint32_t r; asm("fma.rn.bf16x2 %0, %1, %2, %3;" : "=r"(r) : "r"(a), "r"(b), "r"(c)); return r; }
__device__ __forceinline__ void stg128(void* p, uint32_t a, uint32_t b, uint32_t c, uint32_t d) { asm volatile("st.global.v4.u32 [%0], {%1,%2,%3,%4};" :: "l"(p), "r"(a), "r"(b), "r"(c), "r"(d) : "memory"); }

template<int N, int TA, int TB> struct WgmmaSS;
template<int TA, int TB> struct WgmmaSS<8, TA, TB> {
  static __device__ __forceinline__ void mma(float (&d)[4], uint64_t da, uint64_t db, int scale_d) {
    asm volatile("{\n.reg .pred p;\nsetp.ne.b32 p, %6, 0;\n"
      "wgmma.mma_async.sync.aligned.m64n8k16.f32.bf16.bf16 {"
      "%0, %1, %2, %3"
      "}, %4, %5, p, 1, 1, %7, %8;\n}\n"
      :
        "+f"(d[0]), "+f"(d[1]), "+f"(d[2]), "+f"(d[3])
      : "l"(da), "l"(db), "r"(scale_d), "n"(TA), "n"(TB));
  }
};
template<int TA, int TB> struct WgmmaSS<128, TA, TB> {
  static __device__ __forceinline__ void mma(float (&d)[64], uint64_t da, uint64_t db, int scale_d) {
    asm volatile("{\n.reg .pred p;\nsetp.ne.b32 p, %66, 0;\n"
      "wgmma.mma_async.sync.aligned.m64n128k16.f32.bf16.bf16 {"
      "%0, %1, %2, %3, %4, %5, %6, %7, %8, %9, %10, %11, %12, %13, %14, %15, "
      "%16, %17, %18, %19, %20, %21, %22, %23, %24, %25, %26, %27, %28, %29, %30, %31, "
      "%32, %33, %34, %35, %36, %37, %38, %39, %40, %41, %42, %43, %44, %45, %46, %47, "
      "%48, %49, %50, %51, %52, %53, %54, %55, %56, %57, %58, %59, %60, %61, %62, %63"
      "}, %64, %65, p, 1, 1, %67, %68;\n}\n"
      :
        "+f"(d[0]), "+f"(d[1]), "+f"(d[2]), "+f"(d[3]), "+f"(d[4]), "+f"(d[5]), "+f"(d[6]), "+f"(d[7]),
        "+f"(d[8]), "+f"(d[9]), "+f"(d[10]), "+f"(d[11]), "+f"(d[12]), "+f"(d[13]), "+f"(d[14]), "+f"(d[15]),
        "+f"(d[16]), "+f"(d[17]), "+f"(d[18]), "+f"(d[19]), "+f"(d[20]), "+f"(d[21]), "+f"(d[22]), "+f"(d[23]),
        "+f"(d[24]), "+f"(d[25]), "+f"(d[26]), "+f"(d[27]), "+f"(d[28]), "+f"(d[29]), "+f"(d[30]), "+f"(d[31]),
        "+f"(d[32]), "+f"(d[33]), "+f"(d[34]), "+f"(d[35]), "+f"(d[36]), "+f"(d[37]), "+f"(d[38]), "+f"(d[39]),
        "+f"(d[40]), "+f"(d[41]), "+f"(d[42]), "+f"(d[43]), "+f"(d[44]), "+f"(d[45]), "+f"(d[46]), "+f"(d[47]),
        "+f"(d[48]), "+f"(d[49]), "+f"(d[50]), "+f"(d[51]), "+f"(d[52]), "+f"(d[53]), "+f"(d[54]), "+f"(d[55]),
        "+f"(d[56]), "+f"(d[57]), "+f"(d[58]), "+f"(d[59]), "+f"(d[60]), "+f"(d[61]), "+f"(d[62]), "+f"(d[63])
      : "l"(da), "l"(db), "r"(scale_d), "n"(TA), "n"(TB));
  }
};
template<int TA, int TB> struct WgmmaSS<208, TA, TB> {
  static __device__ __forceinline__ void mma(float (&d)[104], uint64_t da, uint64_t db, int scale_d) {
    asm volatile("{\n.reg .pred p;\nsetp.ne.b32 p, %106, 0;\n"
      "wgmma.mma_async.sync.aligned.m64n208k16.f32.bf16.bf16 {"
      "%0, %1, %2, %3, %4, %5, %6, %7, %8, %9, %10, %11, %12, %13, %14, %15, "
      "%16, %17, %18, %19, %20, %21, %22, %23, %24, %25, %26, %27, %28, %29, %30, %31, "
      "%32, %33, %34, %35, %36, %37, %38, %39, %40, %41, %42, %43, %44, %45, %46, %47, "
      "%48, %49, %50, %51, %52, %53, %54, %55, %56, %57, %58, %59, %60, %61, %62, %63, "
      "%64, %65, %66, %67, %68, %69, %70, %71, %72, %73, %74, %75, %76, %77, %78, %79, "
      "%80, %81, %82, %83, %84, %85, %86, %87, %88, %89, %90, %91, %92, %93, %94, %95, "
      "%96, %97, %98, %99, %100, %101, %102, %103"
      "}, %104, %105, p, 1, 1, %107, %108;\n}\n"
      :
        "+f"(d[0]), "+f"(d[1]), "+f"(d[2]), "+f"(d[3]), "+f"(d[4]), "+f"(d[5]), "+f"(d[6]), "+f"(d[7]),
        "+f"(d[8]), "+f"(d[9]), "+f"(d[10]), "+f"(d[11]), "+f"(d[12]), "+f"(d[13]), "+f"(d[14]), "+f"(d[15]),
        "+f"(d[16]), "+f"(d[17]), "+f"(d[18]), "+f"(d[19]), "+f"(d[20]), "+f"(d[21]), "+f"(d[22]), "+f"(d[23]),
        "+f"(d[24]), "+f"(d[25]), "+f"(d[26]), "+f"(d[27]), "+f"(d[28]), "+f"(d[29]), "+f"(d[30]), "+f"(d[31]),
        "+f"(d[32]), "+f"(d[33]), "+f"(d[34]), "+f"(d[35]), "+f"(d[36]), "+f"(d[37]), "+f"(d[38]), "+f"(d[39]),
        "+f"(d[40]), "+f"(d[41]), "+f"(d[42]), "+f"(d[43]), "+f"(d[44]), "+f"(d[45]), "+f"(d[46]), "+f"(d[47]),
        "+f"(d[48]), "+f"(d[49]), "+f"(d[50]), "+f"(d[51]), "+f"(d[52]), "+f"(d[53]), "+f"(d[54]), "+f"(d[55]),
        "+f"(d[56]), "+f"(d[57]), "+f"(d[58]), "+f"(d[59]), "+f"(d[60]), "+f"(d[61]), "+f"(d[62]), "+f"(d[63]),
        "+f"(d[64]), "+f"(d[65]), "+f"(d[66]), "+f"(d[67]), "+f"(d[68]), "+f"(d[69]), "+f"(d[70]), "+f"(d[71]),
        "+f"(d[72]), "+f"(d[73]), "+f"(d[74]), "+f"(d[75]), "+f"(d[76]), "+f"(d[77]), "+f"(d[78]), "+f"(d[79]),
        "+f"(d[80]), "+f"(d[81]), "+f"(d[82]), "+f"(d[83]), "+f"(d[84]), "+f"(d[85]), "+f"(d[86]), "+f"(d[87]),
        "+f"(d[88]), "+f"(d[89]), "+f"(d[90]), "+f"(d[91]), "+f"(d[92]), "+f"(d[93]), "+f"(d[94]), "+f"(d[95]),
        "+f"(d[96]), "+f"(d[97]), "+f"(d[98]), "+f"(d[99]), "+f"(d[100]), "+f"(d[101]), "+f"(d[102]), "+f"(d[103])
      : "l"(da), "l"(db), "r"(scale_d), "n"(TA), "n"(TB));
  }
};
template<int TA, int TB> struct WgmmaSS<224, TA, TB> {
  static __device__ __forceinline__ void mma(float (&d)[112], uint64_t da, uint64_t db, int scale_d) {
    asm volatile("{\n.reg .pred p;\nsetp.ne.b32 p, %114, 0;\n"
      "wgmma.mma_async.sync.aligned.m64n224k16.f32.bf16.bf16 {"
      "%0, %1, %2, %3, %4, %5, %6, %7, %8, %9, %10, %11, %12, %13, %14, %15, "
      "%16, %17, %18, %19, %20, %21, %22, %23, %24, %25, %26, %27, %28, %29, %30, %31, "
      "%32, %33, %34, %35, %36, %37, %38, %39, %40, %41, %42, %43, %44, %45, %46, %47, "
      "%48, %49, %50, %51, %52, %53, %54, %55, %56, %57, %58, %59, %60, %61, %62, %63, "
      "%64, %65, %66, %67, %68, %69, %70, %71, %72, %73, %74, %75, %76, %77, %78, %79, "
      "%80, %81, %82, %83, %84, %85, %86, %87, %88, %89, %90, %91, %92, %93, %94, %95, "
      "%96, %97, %98, %99, %100, %101, %102, %103, %104, %105, %106, %107, %108, %109, %110, %111"
      "}, %112, %113, p, 1, 1, %115, %116;\n}\n"
      :
        "+f"(d[0]), "+f"(d[1]), "+f"(d[2]), "+f"(d[3]), "+f"(d[4]), "+f"(d[5]), "+f"(d[6]), "+f"(d[7]),
        "+f"(d[8]), "+f"(d[9]), "+f"(d[10]), "+f"(d[11]), "+f"(d[12]), "+f"(d[13]), "+f"(d[14]), "+f"(d[15]),
        "+f"(d[16]), "+f"(d[17]), "+f"(d[18]), "+f"(d[19]), "+f"(d[20]), "+f"(d[21]), "+f"(d[22]), "+f"(d[23]),
        "+f"(d[24]), "+f"(d[25]), "+f"(d[26]), "+f"(d[27]), "+f"(d[28]), "+f"(d[29]), "+f"(d[30]), "+f"(d[31]),
        "+f"(d[32]), "+f"(d[33]), "+f"(d[34]), "+f"(d[35]), "+f"(d[36]), "+f"(d[37]), "+f"(d[38]), "+f"(d[39]),
        "+f"(d[40]), "+f"(d[41]), "+f"(d[42]), "+f"(d[43]), "+f"(d[44]), "+f"(d[45]), "+f"(d[46]), "+f"(d[47]),
        "+f"(d[48]), "+f"(d[49]), "+f"(d[50]), "+f"(d[51]), "+f"(d[52]), "+f"(d[53]), "+f"(d[54]), "+f"(d[55]),
        "+f"(d[56]), "+f"(d[57]), "+f"(d[58]), "+f"(d[59]), "+f"(d[60]), "+f"(d[61]), "+f"(d[62]), "+f"(d[63]),
        "+f"(d[64]), "+f"(d[65]), "+f"(d[66]), "+f"(d[67]), "+f"(d[68]), "+f"(d[69]), "+f"(d[70]), "+f"(d[71]),
        "+f"(d[72]), "+f"(d[73]), "+f"(d[74]), "+f"(d[75]), "+f"(d[76]), "+f"(d[77]), "+f"(d[78]), "+f"(d[79]),
        "+f"(d[80]), "+f"(d[81]), "+f"(d[82]), "+f"(d[83]), "+f"(d[84]), "+f"(d[85]), "+f"(d[86]), "+f"(d[87]),
        "+f"(d[88]), "+f"(d[89]), "+f"(d[90]), "+f"(d[91]), "+f"(d[92]), "+f"(d[93]), "+f"(d[94]), "+f"(d[95]),
        "+f"(d[96]), "+f"(d[97]), "+f"(d[98]), "+f"(d[99]), "+f"(d[100]), "+f"(d[101]), "+f"(d[102]), "+f"(d[103]),
        "+f"(d[104]), "+f"(d[105]), "+f"(d[106]), "+f"(d[107]), "+f"(d[108]), "+f"(d[109]), "+f"(d[110]), "+f"(d[111])
      : "l"(da), "l"(db), "r"(scale_d), "n"(TA), "n"(TB));
  }
};

template<int V> struct IntTag { static constexpr int value = V; };
template<bool B> struct BoolTag { static constexpr bool value = B; };
struct cplx { float r, i; };
__device__ __forceinline__ cplx cmul(cplx a, cplx b) { return {fmaf(a.r, b.r, -a.i * b.i), fmaf(a.r, b.i, a.i * b.r)}; }
__device__ __forceinline__ cplx cmulc(cplx a, cplx b) { return {fmaf(a.r, b.r, -a.i * b.i), fmaf(-a.r, b.i, -a.i * b.r)}; }
__device__ __forceinline__ cplx cfma(cplx a, cplx b, cplx c) { return {fmaf(a.r, b.r, fmaf(-a.i, b.i, c.r)), fmaf(a.r, b.i, fmaf(a.i, b.r, c.i))}; }
__device__ __forceinline__ cplx csel(bool p, cplx a, cplx b) { return {p ? a.r : b.r, p ? a.i : b.i}; }
__device__ __forceinline__ cplx cshfl(cplx a, int src) { return {__shfl_sync(0xffffffffu, a.r, src), __shfl_sync(0xffffffffu, a.i, src)}; }

__device__ __forceinline__ void yield_slot(int nap, int zero, uint32_t prev, float& root) {
  asm volatile("{\n.reg .pred p;\nsetp.eq.s32 p, %3, 0;\n@p bra.uni LAB_SKIP;\nnanosleep.u32 %3;\nlop3.b32 %0, %0, %1, %2, 0x78;\nLAB_SKIP:\n}"
    : "+f"(root) : "r"(prev), "r"(zero), "r"(nap));
}
__device__ __forceinline__ void yield_slot(int nap, int zero, uint32_t prev, float& root0, float& root1) {
  asm volatile("{\n.reg .pred p;\nsetp.eq.s32 p, %4, 0;\n@p bra.uni LAB_SKIP;\nnanosleep.u32 %4;\nlop3.b32 %0, %0, %2, %3, 0x78;\nlop3.b32 %1, %1, %2, %3, 0x78;\nLAB_SKIP:\n}"
    : "+f"(root0), "+f"(root1) : "r"(prev), "r"(zero), "r"(nap));
}
__device__ __forceinline__ float tanh_fast(float x) { float y; asm("tanh.approx.f32 %0, %1;" : "=f"(y) : "f"(x)); return y; }
__device__ __forceinline__ void ssm_params(float ar, float ai, float ldt, cplx& lam, cplx& coef2) {
  const float L2E = 1.4426950408889634f;
  const float dt = round_bf(ex2(ldt * L2E));
  const float xr = dt * ar, th = dt * ai;
  const float hi = xr * L2E, lo = fmaf(xr, L2E, -hi) + xr * 1.925963033500011e-8f;
  const float e = ex2(hi) * fmaf(lo, 0.6931471805599453f, 1.0f);
  const float kf = rintf(th * 0.6366197723675814f);
  float r = fmaf(kf, -1.5707963705062866f, th);
  r = fmaf(kf, 4.371138828673793e-8f, r);
  r = fmaf(kf, 1.7151245100058819e-15f, r);
  const int k = (int)kf;
  const float r2 = r * r;
  float sp = fmaf(r2, -1.9515295891e-4f, 8.3321608736e-3f); sp = fmaf(sp, r2, -1.6666654611e-1f); sp = fmaf(sp * r2, r, r);
  float cp = fmaf(r2, 2.443315711809948e-5f, -1.388731625493765e-3f); cp = fmaf(cp, r2, 4.166664568298827e-2f); cp = fmaf(cp, r2, -0.5f); cp = fmaf(cp, r2, 1.0f);
  float sn = (k & 1) ? cp : sp, cs = (k & 1) ? sp : cp;
  sn = (k & 2) ? -sn : sn; cs = ((k + 1) & 2) ? -cs : cs;
  lam.r = e * cs; lam.i = e * sn;
  const bool sw = fabsf(ar) < fabsf(ai);
  const float p = sw ? ai : ar, qq = sw ? ar : ai;
  const float nr = lam.r - 1.0f, ni = lam.i;
  const float t = __fdividef(qq, p), id = __fdividef(2.0f, fmaf(qq, t, p));
  coef2.r = (sw ? fmaf(nr, t, ni) : fmaf(ni, t, nr)) * id;
  coef2.i = (sw ? fmaf(ni, t, -nr) : fmaf(-nr, t, ni)) * id;
}

constexpr uint32_t XFULL = 0, WFULL = 80, WEMPTY = 112, PFULL = 144, PEMPTY = 200, EPOCH = 248, READY = 252;
constexpr int NB_WG0 = 1, NB_ORDER = 2  , NB_FLAG = 4  , NB_CS = 6  , NB_LEAD = 8, NB_HAND = 9;

struct Ptrs { const __nv_bfloat16 *x, *lam_re, *lam_im, *log_dt, *dskip, *bre, *bim, *cre, *cim, *wd; int zero; uint32_t work[NCTA]; };

__device__ __forceinline__ int job_block(int j, int role) {
  return role + (j == 0 ? 10 : j == 1 ? 0 : j == 2 ? (role < 2 ? 8 : 16) : j == 3 ? 24 : 29);
}

__global__ void __launch_bounds__(384, 1) fused_kernel(const __grid_constant__ Maps maps, const __grid_constant__ Ptrs ptrs) {
  extern __shared__ __align__(1024) uint8_t smem_raw[];
  asm volatile(".reg .pred peekp;");
  if (threadIdx.x == 0) { prefetch_map(&maps.x); prefetch_map(&maps.wg); prefetch_map(&maps.wu); }
  const int warp = __shfl_sync(0xffffffffu, threadIdx.x >> 5, 0);
  const int lane = threadIdx.x & 31;
  const uint32_t work = ptrs.work[blockIdx.x];
  const bool spare = work >= 128;
  const int spare_id = work & 3;
  const int m = work & 15;
  const int role = work >> 4;
  const int rank = blockIdx.x & 1;
  const bool is_y = role < 3;
  const int njobs = is_y ? 4 : 5;

  uint32_t sb = smem_u32(smem_raw);
  asm volatile("mov.u32 %0, %0;" : "+r"(sb));
  const uint32_t bars = sb + BAR_OFF;

  if (warp == 8) {
    if (elect_one()) {
      mbar_init(bars + XFULL, 1);
      mbar_init(bars + WFULL, 1);
      asm volatile("fence.mbarrier_init.release.cluster;" ::: "memory");
      if (!spare) {
        mbar_expect_tx(bars + XFULL, SLOT);
        tma4d(sb, &maps.x, 0, 0, m * 4, 0, bars + XFULL);
        mbar_expect_tx(bars + WFULL, SLOT);
        tma2d(sb + WRING_OFF, &maps.wg, role * 64, 0, bars + WFULL);
        tma2d(sb + WRING_OFF + 8192, &maps.wu, role * 64, 0, bars + WFULL);
      }
    }
    __syncwarp();
  } else if (warp == 9) {
    trap_if((sb & 0xffffffu) != SB);
    if (elect_one()) {
#pragma unroll
      for (int i = 14; i < 31; i++) mbar_init(bars + i * 8, i < 18 ? CLUSTER : i < 25 ? 1 : 2 * CLUSTER);
      asm volatile("st.shared.v2.u32 [%0], {0, 0};" :: "r"(bars + EPOCH) : "memory");
      asm volatile("fence.mbarrier_init.release.cluster;" ::: "memory");
    }
    __syncwarp();
  } else if (warp == 10) {
    if (elect_one()) {
#pragma unroll
      for (int i = 1; i < 14; i++) if (i != 10) mbar_init(bars + i * 8, 1);
      asm volatile("fence.mbarrier_init.release.cluster;" ::: "memory");
    }
    __syncwarp();
    if (spare) asm volatile("st.shared.u32 [%0], %1;" :: "r"(sb + ONES_OFF + lane * 4), "r"(0x3f803f80u) : "memory");
    asm volatile("fence.proxy.async.shared::cta;" ::: "memory");
  }
  __syncthreads();
  cluster_sync_relaxed();
  if (warp == 0 && spare) {
    if (elect_one()) {
#pragma unroll 1
      for (int i = 0; i < 4 * S_STAGES; i++) {
        const int st = i >> 2;
        if ((i & 3) == 0) mbar_expect_tx(bars + PFULL + st * 8, O_STAGE);
        tma2d(sb + i * 8192, i & 2 ? &maps.wu : &maps.wg, (spare_id + (st == 5 ? NSPARE : 0)) * 64, (st == 5 ? 0 : st * 128) + (i & 1) * 64, bars + PFULL + st * 8);
      }
    }
    __syncwarp();
  } else if (warp == 0) {
    if (elect_one()) {
#pragma unroll
      for (int k = 1; k < 10; k++) {
        mbar_expect_tx(bars + XFULL + k * 8, SLOT);
        tma4d(sb + k * SLOT, &maps.x, k * 64, 0, m * 4, 0, bars + XFULL + k * 8);
        if (k < 4) {
          mbar_expect_tx(bars + WFULL + k * 8, SLOT);
          tma2d_mc(sb + WRING_OFF + k * SLOT + rank * 8192, rank ? &maps.wu : &maps.wg, role * 64, k * 64, bars + WFULL + k * 8);
        }
      }
    }
    __syncwarp();
  }

  if (warp >= 8) {
    reg_dealloc<40>();
    if (spare) {
      if (warp == 8) {
        int s = 0; uint32_t ph = 0;
#pragma unroll 1
        for (int u = spare_id + NSPARE; u < 27; u += NSPARE) {
#pragma unroll 1
          for (int kb = u < 2 * NSPARE ? 1 : 0; kb < 5; kb++) {
            mbar_wait(bars + PEMPTY + s * 8, ph);
            if (elect_one()) {
              mbar_expect_tx(bars + PFULL + s * 8, O_STAGE);
#pragma unroll 1
              for (int i = 0; i < 4; i++) {
                tma2d(sb + s * O_STAGE + i * 8192, i & 2 ? &maps.wu : &maps.wg, u * 64, kb * 128 + (i & 1) * 64, bars + PFULL + s * 8);
              }
            }
            __syncwarp();
            if (++s == S_STAGES) { s = 0; ph ^= 1; }
          }
        }
#pragma unroll 1
        for (int i = spare_id; i < 64; i += NSPARE) {
          if (elect_one()) {
            prefetch_l2(ptrs.cre + (size_t)i * (P_ * D_ / 64), P_ * D_ * 2 / 64);
            prefetch_l2(ptrs.cim + (size_t)i * (P_ * D_ / 64), P_ * D_ * 2 / 64);
            prefetch_l2(ptrs.wd + (size_t)i * (F_ * D_ / 64), F_ * D_ * 2 / 64);
          }
          __syncwarp();
        }
      } else if (warp == 11 && lane == 0) {
        uint32_t ep;
        asm volatile("atom.relaxed.gpu.global.add.u32 %0, [%1], 1;" : "=r"(ep) : "l"(&g_ticket) : "memory");
        sts_release(bars + EPOCH, ep / NCTA + 1u);
      }
      __syncwarp();
    } else {
      if (warp == 8) {
      int j = 0, kb = 4;
#pragma unroll 1
      for (int it = 4; it < njobs * 10; it++) {
        const int b = job_block(j, role);
        const bool isB = b < 10;
        const int blk = (isB ? b : b - 10) * 64;
        const int s = it & 3;
        mbar_wait(bars + WEMPTY + s * 8, ((it >> 2) & 1) ^ 1);
        if (elect_one()) {
          const uint32_t dst = sb + WRING_OFF + s * SLOT, fb = bars + WFULL + s * 8;
          const int c0 = isB ? kb * 64 : blk, c1 = isB ? blk : kb * 64;
          mbar_expect_tx(fb, SLOT);
          tma2d_mc(dst + rank * 8192, isB ? (rank ? &maps.bim : &maps.bre) : (rank ? &maps.wu : &maps.wg), c0, c1, fb);
        }
        __syncwarp();
        if (++kb == 10) { kb = 0; j++; }
      }
      }
      uint32_t ep = 0;
      if (warp == 11 && lane == 0) {
        asm volatile("atom.relaxed.gpu.global.add.u32 %0, [%1], 1;" : "=r"(ep) : "l"(&g_ticket) : "memory");
        if (is_y) { prefetch_map(&maps.cre0); prefetch_map(&maps.cre1); prefetch_map(&maps.cim0); prefetch_map(&maps.cim1); }
        else { prefetch_map(&maps.wd); prefetch_map(&maps.out); prefetch_map(&maps.cre2); }
        prefetch_map(rank ? &maps.bim : &maps.bre);
        sts_release(bars + EPOCH, ep / NCTA + 1u);
      }
      __syncwarp();
      ep = smem_wait_bits(bars + EPOCH, 0xffffffffu);
      if (warp > 8) {
        mbar_wait(bars + XFULL + 9 * 8, 0);
        const int idx = role * 16 + m, r0 = (warp == 10 ? 8 : (warp - 9) * 2) + (lane >> 4);
        const uint4* src = reinterpret_cast<const uint4*>(idx < 64 ? ptrs.bre + (size_t)idx * 10 * D_ : ptrs.bim + (size_t)(idx - 64) * 10 * D_) + r0 * (D_ / 8) + (lane & 15);
        int st = (idx & 63) * 10 + r0;
#pragma unroll 1
        for (int r = warp == 10; r < 2; r++, src += 2 * (D_ / 8), st += 2) {
          uint4 v[5];
#pragma unroll
          for (int i = 0; i < 5; i++) v[i] = __ldg(src + i * 16);
          float s0 = 0.f, s1 = 0.f;
#pragma unroll
          for (int i = 0; i < 5; i++) {
            s0 += (bf_lo(v[i].x) + bf_lo(v[i].y)) + (bf_lo(v[i].z) + bf_lo(v[i].w));
            s1 += (bf_hi(v[i].x) + bf_hi(v[i].y)) + (bf_hi(v[i].z) + bf_hi(v[i].w));
          }
          s0 += s1;
#pragma unroll
          for (int o = 8; o; o >>= 1) s0 += __shfl_xor_sync(0xffffffffu, s0, o);
          if ((lane & 15) == 0) st_tagged(&g_cs[(st >> 6) * 128 + (idx < 64 ? 0 : 64) + (st & 63)], s0, ep);
        }
        __syncwarp();
      }
      if (warp == 9 || warp == 10) {
        const int wg = warp - 9;
        uint2 dv;
        asm volatile("ld.global.nc.v2.u32 {%0, %1}, [%2];" : "=r"(dv.x), "=r"(dv.y) : "l"(reinterpret_cast<const uint2*>(ptrs.dskip + max(role - 3, 0) * 128) + lane));
        reinterpret_cast<uint2*>(smem_raw + ONES_OFF)[lane] = dv;
        int j = wg ^ 1;
#pragma unroll 1
        while (j < njobs) {
          const int b = job_block(j, role);
          const uint2* src = g_cs + b * 128 + lane * 4;
          const uint2* src2 = g_stat + m * 128 + lane * 4;
          uint4 v0 = make_uint4(0u, ~ep, 0u, 0u), v1 = v0, v2 = make_uint4(0u, j < 2 ? ~ep : ep, 0u, ep), v3 = make_uint4(0u, ep, 0u, ep);
          const uint32_t t0 = clock32();
          while (true) {
            const bool m0 = ((v0.y ^ ep) | (v0.w ^ ep) | (v1.y ^ ep) | (v1.w ^ ep)) != 0, m1 = ((v2.y ^ ep) | (v2.w ^ ep) | (v3.y ^ ep) | (v3.w ^ ep)) != 0;
            if (m0) { v0 = ld_relaxed128(src); v1 = ld_relaxed128(src + 2); }
            if (m1) { v2 = ld_relaxed128(src2); v3 = ld_relaxed128(src2 + 2); }
            if (!__any_sync(0xffffffffu, m0 || m1) || clock32() - t0 > 1000000000u) break;
          }
          if (j < 2) {
            float4* dst = reinterpret_cast<float4*>(smem_raw + STAT_OFF) + lane * 2;
            dst[0] = make_float4(-bf_lo(v2.x), rcp(bf_hi(v2.x)), -bf_lo(v2.z), rcp(bf_hi(v2.z)));
            dst[1] = make_float4(-bf_lo(v3.x), rcp(bf_hi(v3.x)), -bf_lo(v3.z), rcp(bf_hi(v3.z)));
          }
          reinterpret_cast<uint4*>(smem_raw + CS_OFF + wg * 512)[lane] = make_uint4(v0.x, v0.z, v1.x, v1.z);
          bar_arrive(NB_CS + wg, 160);
          bar_sync(NB_FLAG + wg, 160);
          fence_proxy_async();
          if (lane == 0) {
            if (b < 10) red_release_add(&g_flag[m * 32 + (b < 8 ? 27 : 30)], 1u);
            else st_release(&g_flag[m * 32 + b - 10], ep);
          }
          __syncwarp();
          j += 2;
        }
      } else {
        const uint32_t target = ep * (lane < 27 ? 1u : lane == 27 ? 8u : lane == 30 ? 2u : 12u);
        const uint32_t all = is_y ? 0x48000000u : 0x3fffffffu;
        const uint32_t need = warp == 8 ? all : is_y ? 0x08000000u : 0x08003fffu;
        uint32_t ready = 0;
        const uint32_t t0 = clock32();
        while ((ready & need) != need) {
          const uint32_t now = __ballot_sync(0xffffffffu, ld_relaxed(&g_flag[m * 32 + lane]) == target || clock32() - t0 > 1000000000u) & all;
          if (now != ready) {
            if ((now ^ ready) & 0x4fffffffu) {
              asm volatile("fence.acquire.gpu;" ::: "memory");
              fence_proxy_async();
              __syncwarp();
            }
            ready = now;
            if (warp == 8) sts_release(bars + READY, ready);
          } else if ((ready & 0x0fffffffu) != 0x0fffffffu) {
            __nanosleep(200);
          }
        }
        if (warp == 11) {
      if (is_y) {
        const int d0 = role * YN0, half = role == 2 ? YN2 / 2 : YN0 / 2, ystage = SLOT + half * 256;
        int s = 0; uint32_t ph = 0;
#pragma unroll 1
        for (int kk = YS; kk < 20; kk++) {
          mbar_wait(bars + PEMPTY + s * 8, ph);
          if (kk == 16 && !(ready >> 30)) { smem_wait_bits(bars + READY, 1u << 30); fence_proxy_async(); }
          if (elect_one()) {
            const uint32_t dst = sb + s * ystage, fb = bars + PFULL + s * 8;
            const bool im = kk & 1;
            const int kc = (kk >> 1) * 64;
            mbar_expect_tx(fb, ystage);
            bulk_load(dst, g_hT + (m * 20 + kk) * 1024, SLOT, fb);
            const CUtensorMap* mc = role == 2 ? (im ? &maps.cim0 : &maps.cre0) : (im ? &maps.cim1 : &maps.cre1);
            tma2d_mc(dst + SLOT + rank * half * 128, mc, kc, d0 + rank * half, fb);
          }
          __syncwarp();
          if (++s == Y_STAGES) { s = 0; ph ^= 1; }
        }
      } else {
        const int n0 = (role - 3) * 128;
        int s = 0; uint32_t ph = 0;
#pragma unroll 1
        for (int kk = 0; kk < 27; kk++) {
          if (YS && kk == O_SOLO) {
#pragma unroll 1
            for (int t = 0; t < YS; t++) {
              mbar_wait(bars + PEMPTY + s * 8, ph);
              if (elect_one()) {
                const uint32_t dst = sb + s * O_STAGE, fb = bars + PFULL + s * 8;
                mbar_expect_tx(fb, O_STAGE);
                bulk_load(dst, g_hT + (m * 20 + t) * 1024, SLOT, fb);
                tma2d_mc(dst + SLOT + rank * 8192, (t & 1) ? &maps.cim2 : &maps.cre2, (t >> 1) * 64, n0 + rank * 64, fb);
              }
              __syncwarp();
              if (++s == O_STAGES) { s = 0; ph ^= 1; }
            }
          }
          mbar_wait(bars + PEMPTY + s * 8, ph);
          const uint32_t bit = 1u << kk;
          if (!(ready & bit)) {
            ready |= __shfl_sync(0xffffffffu, smem_wait_bits(bars + READY, bit), 0);
            fence_proxy_async();
          }
          if (elect_one()) {
            const uint32_t dst = sb + s * O_STAGE, fb = bars + PFULL + s * 8;
            mbar_expect_tx(fb, O_STAGE);
            bulk_load(dst, g_H + (m * 27 + kk) * 1024, SLOT, fb);
            tma5d_mc(dst + SLOT + rank * 8192, &maps.wd, n0 + rank * 64, kk * 2, fb);
          }
          __syncwarp();
          if (++s == O_STAGES) { s = 0; ph ^= 1; }
        }
      }
        }
      }
    }
    cluster_sync_relaxed();
  } else {
    const int wg = warp >> 2;
    const int w4 = warp & 3;
    const int q = lane & 3, r8 = lane >> 2;
    const float2* s_stat = reinterpret_cast<const float2*>(smem_raw + STAT_OFF);
    float* s_cs = reinterpret_cast<float*>(smem_raw + CS_OFF + wg * 512);

    if (spare) {
      const uint32_t ep = smem_wait_bits(bars + EPOCH, 0xffffffffu);
      int s = 0; uint32_t ph = 0;
#pragma unroll 1
      for (int u = spare_id; u < 27; u += NSPARE) {
        float cs[4];
        zero_regs(cs);
#pragma unroll 1
        for (int kb = 0; kb < 5; kb++) {
          mbar_wait(bars + PFULL + s * 8, ph);
          const uint32_t ad = (SB >> 4) + s * (O_STAGE >> 4) + wg * 1024;
          wgmma_fence();
#pragma unroll
          for (int k = 0; k < 8; k++) WgmmaSS<8, 1, 0>::mma(cs, mkdesc(ad + DMN + k * 128), (uint64_t)((SB + ONES_OFF) >> 4), 1);
          wgmma_commit();
          wgmma_wait<0>();
          if ((threadIdx.x & 127) < CLUSTER) mbar_arrive(bars + PEMPTY + s * 8);
          if (++s == S_STAGES) { s = 0; ph ^= 1; }
        }
        fence_regs(cs);
        if (q < 2) st_tagged(&g_cs[(10 + u) * 128 + wg * 64 + w4 * 16 + q * 8 + r8], q ? cs[2] : cs[0], ep);
      }
      cluster_sync_relaxed();
      return;
    }
    const bool rel = (threadIdx.x & 127) < CLUSTER;
    uint32_t rbars;
    asm volatile("mapa.shared::cluster.u32 %0, %1, %2;" : "=r"(rbars) : "r"(bars), "r"(threadIdx.x & 1));

    const int lane_rel = (threadIdx.x & 127) / CLUSTER;
    const uint32_t prel = rbars + PEMPTY + (lane_rel & 7) * 8;

    const int slab = wg * 4 + w4;
    const int c0 = is_y ? role * YN0 : (role - 3) * 128;
    uint32_t xr[2][16];
    uint4* kcp = g_kc + ((role & 1) * 16 + m) * 7 * 128 + (threadIdx.x & 127);

    float acc[2][64];
    auto mma_half = [&](auto isb_tag, uint32_t xd, uint32_t wd, int k0, bool accum) {
      constexpr bool ISB = decltype(isb_tag)::value;
#pragma unroll
      for (int k = k0; k < k0 + 2; k++) {
        if constexpr (ISB) {
          WgmmaSS<128, 0, 0>::mma(acc[0], mkdesc(wd + k * 2), mkdesc(xd + k * 2), accum || k);
          WgmmaSS<128, 0, 0>::mma(acc[1], mkdesc(wd + 512 + k * 2), mkdesc(xd + k * 2), accum || k);
        } else {
          WgmmaSS<128, 0, 1>::mma(acc[0], mkdesc(xd + k * 2), mkdesc(wd + k * 128), accum || k);
          WgmmaSS<128, 0, 1>::mma(acc[1], mkdesc(xd + 512 + k * 2), mkdesc(wd + k * 128), accum || k);
        }
      }
    };
    auto mainloop = [&](auto isb_tag, auto first_tag, int j) {
      constexpr bool ISB = decltype(isb_tag)::value, FIRST = decltype(first_tag)::value;
      constexpr uint32_t XD0 = (SB >> 4) + DK, WD0 = ((SB + WRING_OFF) >> 4) + (ISB ? DK : DMN);
      constexpr uint32_t WD_X = 0x1800, F_X = 0x30, E_X = 0xf0;
      static_assert(O_LEAD <= 5 && Y_LEAD <= 4, "the streamed segment must release every stage that is refilled");
      static_assert((WD0 ^ WD_X) == WD0 + 2048 && ((WD0 + 1024) ^ WD_X) == WD0 + 3072, "ring layout");
      static_assert((WFULL ^ F_X) == WFULL + 16 && ((WFULL + 8) ^ F_X) == WFULL + 24 && (WEMPTY ^ E_X) == WEMPTY + 16 && ((WEMPTY + 8) ^ E_X) == WEMPTY + 24, "barrier layout");
      const int s0 = (j & 1) * 2;
      uint32_t wd = WD0 + s0 * 1024, fb = bars + WFULL + s0 * 8, eb = rbars + WEMPTY + s0 * 8;
      uint32_t xd = XD0;
      {
        uint32_t pair = j * 5;
        int trig = (j == njobs - 1 && lane_rel < (is_y ? (role < 2 ? 3 : 2) : 4)) ? (is_y ? max(lane_rel + 2, 3) : lane_rel + 1) : -1;
        asm volatile("" : "+r"(wd), "+r"(fb), "+r"(eb), "+r"(pair), "+r"(trig));
        if (!FIRST) bar_sync(NB_ORDER + wg, 256);
        peek(fb, (pair >> 1) & 1);
#pragma unroll 1
        for (int i = 0; i < 5; i++) {
          const uint32_t par = (pair >> 1) & 1;
          pair++;
          if (FIRST) mbar_wait(bars + XFULL + i * 16, 0);
          wait_peeked(fb, par);
          wgmma_fence();
          mma_half(isb_tag, xd, wd, 0, i != 0);
          wgmma_commit();
          wgmma_wait<1>();
          arrive_if(rel && i != 0, (eb ^ E_X) + 8);
          peek(fb + 8, par);
          arrive_if(i == trig, prel);
          mma_half(isb_tag, xd, wd, 2, true);
          wgmma_commit();
          if (FIRST) mbar_wait(bars + XFULL + i * 16 + 8, 0);
          wait_peeked(fb + 8, par);
          wgmma_fence();
          mma_half(isb_tag, xd + 1024, wd + 1024, 0, true);
          wgmma_commit();
          wgmma_wait<1>();
          arrive_if(rel, eb);
          fb ^= F_X; eb ^= E_X;
          peek(fb, (pair >> 1) & 1);
          mma_half(isb_tag, xd + 1024, wd + 1024, 2, true);
          wgmma_commit();
          xd += 2048; wd ^= WD_X;
        }
        bar_arrive_if(j != 4, NB_ORDER + (wg ^ 1));
        wgmma_wait<0>();
        arrive_if(rel, (eb ^ E_X) + 8);
        if (!ISB && !FIRST && (j & 2) && !is_y) {
          int ln = lane;
          asm volatile("" : "+r"(ln));
          const int rho = (ln & 1) + 4 * (slab & 1) + ((ln >> 2) & 2) + 8 * (4 * (slab >> 1) + ((ln >> 1) & 3));
          const uint32_t base = sb + (role - 3) * 2 * SLOT + rho * 128, sw = ((ln >> 4) ^ (rho & 7) ^ (ln & 6)) << 4;
#pragma unroll
          for (int jj = 0; jj < 16; jj += 2)
            ldsm4(xr[0][jj], xr[1][jj], xr[0][jj + 1], xr[1][jj + 1], base + (jj >> 3) * SLOT + (sw ^ ((jj & 7) << 4)));
          if (j == 3) bar_sync(NB_WG0, 128);
        }
        arrive_if(j >= njobs - 2 && trig < 0 && lane_rel < (is_y ? Y_STAGES : O_STAGES), prel);
      }
      fence_regs(acc[0]); fence_regs(acc[1]);
    };

    if (wg == 1) mainloop(BoolTag<false>{}, BoolTag<true>{}, 0);
    reg_alloc<232>();
#pragma unroll
    for (int i = 0; i < 16; i++) { xr[0][i] = 0; xr[1][i] = 0; }
    if (wg == 0) {
      const int p = min((role + (lane < 16 ? 8 : 0)) * 64 + w4 * 16 + (lane & 15), P_ - 1);
      uint32_t raw[3];
      asm volatile("ld.global.nc.u16 %0, [%1];" : "=r"(raw[0]) : "l"(ptrs.lam_re + p));
      asm volatile("ld.global.nc.u16 %0, [%1];" : "=r"(raw[1]) : "l"(ptrs.lam_im + p));
      asm volatile("ld.global.nc.u16 %0, [%1];" : "=r"(raw[2]) : "l"(ptrs.log_dt + p));
      {
        const int rho = role * 16 + w4 * 4 + (lane >> 3);
        const uint4* row = reinterpret_cast<const uint4*>(smem_raw + rho * 128) + (lane & 7);
        float s0 = 0.f, s1 = 0.f, q0 = 0.f, q1 = 0.f, x0 = 0.f;
#pragma unroll 1
        for (int kb = 0; kb < 10; kb += 2, row += 2 * (SLOT / 16)) {
          mbar_wait(bars + XFULL + kb * 8, 0);
          mbar_wait(bars + XFULL + kb * 8 + 8, 0);
          const uint4 v = row[0], u = row[SLOT / 16];
          if (kb == 0) x0 = __shfl_sync(0xffffffffu, bf_lo(v.x), lane & ~7);
          const uint32_t w[8] = {v.x, v.y, v.z, v.w, u.x, u.y, u.z, u.w};
#pragma unroll
          for (int k = 0; k < 8; k++) { const float a = bf_lo(w[k]) - x0, c = bf_hi(w[k]) - x0; s0 += a; s1 += c; q0 = fmaf(a, a, q0); q1 = fmaf(c, c, q1); }
        }
        s0 += s1; q0 += q1;
#pragma unroll
        for (int o = 1; o < 8; o <<= 1) { s0 += __shfl_xor_sync(0xffffffffu, s0, o); q0 += __shfl_xor_sync(0xffffffffu, q0, o); }
        const float mean = s0 * (1.0f / D_);
        float den;
        asm("sqrt.approx.f32 %0, %1;" : "=f"(den) : "f"(round_bf(round_bf(fmaxf(fmaf(-mean, mean, q0 * (1.0f / D_)), 0.f)) + 1e-5f)));
        const uint32_t ep = smem_wait_bits(bars + EPOCH, 0xffffffffu);
        if ((lane & 7) == 0) st_tagged(&g_stat[m * 128 + rho], __uint_as_float(pack_bf16(x0 + mean, den)), ep);
        __syncwarp();
      }
      cplx lam, cf;
      asm volatile("" : "+r"(raw[0]), "+r"(raw[1]), "+r"(raw[2]));
      ssm_params(bf_lo(raw[0]), bf_lo(raw[1]), bf_lo(raw[2]), lam, cf);
#pragma unroll 1
      for (int pass = role < 2 ? 0 : 2; pass < 4; pass++) {
        const int src = r8 + 8 * (pass ^ 1);
        const cplx l1 = cshfl(lam, src), c1 = cshfl(cf, src), zero = {0.f, 0.f}, one = {1.f, 0.f};
        cplx l32 = l1;
#pragma unroll
        for (int t = 0; t < 5; t++) l32 = cmul(l32, l32);
        const cplx l64 = cmul(l32, l32), l128 = cmul(l64, l64), l256 = cmul(l128, l128);
        const int tl = (lane & 7) * 4 + (lane >> 3);
        const cplx k[7] = {l1, c1, csel(q >= 1, l32, zero), csel(q >= 2, l64, zero), cshfl(cmul(l256, l256), tl),
                           cshfl(cmul(csel(q & 1, l128, one), csel(q & 2, l256, one)), tl), cmul(c1, cmul(csel(q & 1, l32, one), csel(q & 2, l64, one)))};
#pragma unroll
        for (int t = 0; t < 7; t++) {
          xr[1][2 * t] = xr[0][2 * t]; xr[1][2 * t + 1] = xr[0][2 * t + 1];
          xr[0][2 * t] = __float_as_uint(k[t].r); xr[0][2 * t + 1] = __float_as_uint(k[t].i);
        }
        if (pass == 1) {
#pragma unroll
          for (int t = 0; t < 7; t++) stg128(kcp + t * 128, xr[0][2 * t], xr[1][2 * t], xr[0][2 * t + 1], xr[1][2 * t + 1]);
          bar_arrive(NB_LEAD, 256);
        }
      }
    }

#pragma unroll 1
    for (int j = wg ^ 1; j < njobs; j += 2) {
    const int b = job_block(j, role);
    if (b < 10) {
      if (j == 2) {
        bar_sync(NB_LEAD, 256);
#pragma unroll
        for (int t = 0; t < 7; t++)
          asm volatile("ld.global.v4.u32 {%0,%1,%2,%3}, [%4];" : "=r"(xr[0][2 * t]), "=r"(xr[1][2 * t]), "=r"(xr[0][2 * t + 1]), "=r"(xr[1][2 * t + 1]) : "l"(kcp + t * 128) : "memory");
      }
      mainloop(BoolTag<true>{}, BoolTag<false>{}, j);
      auto kc = [&](int h, int i) { return cplx{__uint_as_float(xr[h][2 * i]), __uint_as_float(xr[h][2 * i + 1])}; };
      cplx lamA = kc(0, 0), lamB = kc(1, 0);
      bar_sync(NB_CS + wg, 160);
      const uint32_t ep = lds_volatile(bars + EPOCH);
      const int pA = b * 64 + w4 * 16 + r8;
      const cplx csA = {s_cs[w4 * 16 + r8], s_cs[64 + w4 * 16 + r8]}, csB = {s_cs[w4 * 16 + r8 + 8], s_cs[64 + w4 * 16 + r8 + 8]};
      cplx aA = {0.f, 0.f}, aB = {0.f, 0.f};
      const int naps = j == 2 ? NAPS : ptrs.zero;
#pragma unroll
      for (int i = 0; i < 16; i++) {
        const float4 st = *reinterpret_cast<const float4*>(s_stat + 8 * i + 2 * q);
#pragma unroll
        for (int e = 0; e < 2; e++) {
          const float mb = e ? st.z : st.x, rd = e ? st.w : st.y;
          const int ia = 4 * i + e, ib = ia + 2;
          acc[0][ia] = fmaf(mb, csA.r, acc[0][ia]) * rd; acc[1][ia] = fmaf(mb, csA.i, acc[1][ia]) * rd;
          acc[0][ib] = fmaf(mb, csB.r, acc[0][ib]) * rd; acc[1][ib] = fmaf(mb, csB.i, acc[1][ib]) * rd;
          aA = cfma(lamA, aA, cplx{acc[0][ia], acc[1][ia]});
          aB = cfma(lamB, aB, cplx{acc[0][ib], acc[1][ib]});
        }
      }
      aA = cfma(kc(0, 2), cshfl(aA, lane - 1), aA); aB = cfma(kc(1, 2), cshfl(aB, lane - 1), aB);
      aA = cfma(kc(0, 3), cshfl(aA, lane - 2), aA); aB = cfma(kc(1, 3), cshfl(aB, lane - 2), aB);
      if (q == 3 && m < 15) {
        const uint64_t tg = (uint64_t)ep << 32;
        asm volatile("st.relaxed.gpu.global.v2.u64 [%0], {%1, %2};" :: "l"(&g_agg[m * P_ + pA]), "l"(tg | __float_as_uint(aA.r)), "l"(tg | __float_as_uint(aA.i)) : "memory");
        asm volatile("st.relaxed.gpu.global.v2.u64 [%0], {%1, %2};" :: "l"(&g_agg[m * P_ + pA + 8]), "l"(tg | __float_as_uint(aB.r)), "l"(tg | __float_as_uint(aB.i)) : "memory");
      }
      cplx eA = csel(q, cshfl(aA, lane - 1), cplx{0.f, 0.f}), eB = csel(q, cshfl(aB, lane - 1), cplx{0.f, 0.f});
      cplx cfA = kc(0, 1), cfB = kc(1, 1);
      yield_slot(ptrs.zero, ptrs.zero, __float_as_uint(eA.r), cfA.i, cfB.i);
      eA = cmulc(cfA, eA); eB = cmulc(cfB, eB);
#pragma unroll
      for (int i = 0; i < 16; i++) {
#pragma unroll
        for (int e = 0; e < 2; e++) {
          const cplx ta = cmulc(cfA, cplx{acc[0][4 * i + e], acc[1][4 * i + e]});
          const cplx tb = cmulc(cfB, cplx{acc[0][4 * i + 2 + e], acc[1][4 * i + 2 + e]});
          acc[0][4 * i + e] = ta.r; acc[1][4 * i + e] = ta.i; acc[0][4 * i + 2 + e] = tb.r; acc[1][4 * i + 2 + e] = tb.i;
        }
      }
      cplx gA = {0.f, 0.f}, gB = {0.f, 0.f};
      {
        uint4 vA[4], vB[4];
        const int lo = lane >> 3;
        const uint4* ap = &g_agg[(m - 1 - lo) * P_ + b * 64 + w4 * 16 + (lane & 7)];
#pragma unroll
        for (int t = 0; t < 4; t++) { const uint32_t tg = m - 1 - lo - 4 * t >= 0 ? ~ep : ep; vA[t] = make_uint4(0u, tg, 0u, ep); vB[t] = make_uint4(0u, ep, 0u, ep); }
        const uint32_t t0 = clock32();
        while (true) {
          bool miss = false;
#pragma unroll
          for (int t = 0; t < 4; t++) {
            const bool mt = ((vA[t].y ^ ep) | (vA[t].w ^ ep) | (vB[t].y ^ ep) | (vB[t].w ^ ep)) != 0;
            if (mt) { vA[t] = ld_relaxed128(ap - 4 * t * P_); vB[t] = ld_relaxed128(ap - 4 * t * P_ + 8); }
            miss |= mt;
          }
          if (!__any_sync(0xffffffffu, miss) || clock32() - t0 > 1000000000u) break;
        }
#pragma unroll
        for (int t = 3; t >= 0; t--) {
          gA = cfma(kc(0, 4), gA, cplx{__uint_as_float(vA[t].x), __uint_as_float(vA[t].z)});
          gB = cfma(kc(1, 4), gB, cplx{__uint_as_float(vB[t].x), __uint_as_float(vB[t].z)});
        }
      }
      gA = cmul(gA, kc(0, 5)); gB = cmul(gB, kc(1, 5));
#pragma unroll
      for (int o = 8; o < 32; o <<= 1) {
        gA.r += __shfl_xor_sync(0xffffffffu, gA.r, o); gA.i += __shfl_xor_sync(0xffffffffu, gA.i, o);
        gB.r += __shfl_xor_sync(0xffffffffu, gB.r, o); gB.i += __shfl_xor_sync(0xffffffffu, gB.i, o);
      }
      gA = cshfl(gA, r8); gB = cshfl(gB, r8);
      gA = cmulc(gA, kc(0, 6)); gB = cmulc(gB, kc(1, 6));
      gA.r += eA.r; gA.i += eA.i; gB.r += eB.r; gB.i += eB.i;
      lamA.i = -lamA.i; lamB.i = -lamB.i;
      uint4* hp = g_hT + (m * 20 + b * 2) * 1024 + (w4 * 16 + r8) * 4 + (q ^ (r8 >> 1));
#pragma unroll
      for (int c = 0; c < 4; c++) {
        uint32_t oAr[4], oAi[4], oBr[4], oBi[4];
#pragma unroll
        for (int ii = 0; ii < 4; ii++) {
          const int i = c * 4 + ii;
          const cplx a0 = cfma(lamA, gA, cplx{acc[0][4 * i], acc[1][4 * i]});
          const cplx b0 = cfma(lamB, gB, cplx{acc[0][4 * i + 2], acc[1][4 * i + 2]});
          gA = cfma(lamA, a0, cplx{acc[0][4 * i + 1], acc[1][4 * i + 1]});
          gB = cfma(lamB, b0, cplx{acc[0][4 * i + 3], acc[1][4 * i + 3]});
          oAr[ii] = pack_bf16(a0.r, gA.r); oAi[ii] = pack_bf16(a0.i, gA.i);
          oBr[ii] = pack_bf16(b0.r, gB.r); oBi[ii] = pack_bf16(b0.i, gB.i);
          yield_slot((ii & 1) ? naps : ptrs.zero, ptrs.zero, oBi[ii], gA.i, gB.i);
        }
        stg128(hp + c * 256, oAr[0], oAr[1], oAr[2], oAr[3]);
        stg128(hp + c * 256 + 32, oBr[0], oBr[1], oBr[2], oBr[3]);
        stg128(hp + c * 256 + 1024, oAi[0], oAi[1], oAi[2], oAi[3]);
        stg128(hp + c * 256 + 1056, oBi[0], oBi[1], oBi[2], oBi[3]);
      }
    } else {
      if (j > 0) mainloop(BoolTag<false>{}, BoolTag<false>{}, j);
      const int ft = b - 10;
      uint4* hb = g_H + (m * 27 + ft) * 1024 + ((w4 >> 1) * 32 + (r8 >> 1) * 8 + (w4 & 1) * 4 + (r8 & 1)) * 4;
      uint4* hp[2] = {hb + (q ^ ((w4 & 1) * 2)), hb + 8 + (q ^ ((w4 & 1) * 2 + 1))};
      bar_sync(NB_CS + wg, 160);
      const int nap = j == 3 ? (is_y ? ptrs.zero : NAP3) : j == 0 ? NAP0 : NAP;
      float mb[4], k0[4], k1[4];
#pragma unroll
      for (int rr = 0; rr < 4; rr++) {
        const float2 st = s_stat[(rr >> 1) * 64 + w4 * 16 + (rr & 1) * 8 + r8];
        mb[rr] = st.x; k0[rr] = st.y * 0.7978845608028654f; k1[rr] = k0[rr] * 0.044715f * st.y * st.y;
      }
#pragma unroll
      for (int a = 0; a < 2; a++) {
        float2 cg[4], cu[4];
#pragma unroll
        for (int jj = 0; jj < 4; jj++) {
          cg[jj] = *reinterpret_cast<const float2*>(s_cs + (a * 4 + jj) * 8 + q * 2);
          cu[jj] = *reinterpret_cast<const float2*>(s_cs + 64 + (a * 4 + jj) * 8 + q * 2);
        }
#pragma unroll
        for (int rr = 0; rr < 4; rr++) {
          const int mi = rr >> 1, hf = rr & 1;
          uint32_t o[4];
#pragma unroll
          for (int jj = 0; jj < 4; jj++) {
            const int i0 = 4 * (a * 4 + jj) + hf * 2;
            const float g0 = fmaf(mb[rr], cg[jj].x, acc[mi][i0]), g1 = fmaf(mb[rr], cg[jj].y, acc[mi][i0 + 1]);
            const float w0 = g0 * fmaf(mb[rr], cu[jj].x, acc[mi][32 + i0]), w1 = g1 * fmaf(mb[rr], cu[jj].y, acc[mi][32 + i0 + 1]);
            const float t0 = tanh_fast(g0 * fmaf(g0 * g0, k1[rr], k0[rr])), t1 = tanh_fast(g1 * fmaf(g1 * g1, k1[rr], k0[rr]));
            o[jj] = pack_bf16(fmaf(w0, t0, w0), fmaf(w1, t1, w1));
          }
          stg128(hp[hf] + mi * 256 + a * 512, o[0], o[1], o[2], o[3]);
          if (a * 4 + rr < 7) yield_slot(nap, ptrs.zero, o[3], mb[(rr + 1) & 3]);
        }
      }
    }
    bar_arrive(NB_FLAG + wg, 160);
    }

    peek_clear();
    const uint32_t par = lds_volatile(bars + EPOCH) & 1u;
    if (is_y) {
      auto y_job = [&](auto yn_tag) {
      constexpr int YN = decltype(yn_tag)::value, Y_STAGE = SLOT + YN * 128;
      float ya[YN / 2];
      if (wg == 1) bar_sync(NB_ORDER + 1, 256);
      uint32_t off = 0, fb = bars + PFULL, eb = 0, ph = 0;
      const uint32_t ad0 = (SB >> 4) + wg * 512 + DMN64;
      bool accum = false;
#pragma unroll 1
      for (int seg = 0; seg < 2; seg++) {
        if (seg == 1 && wg == 1) bar_sync(NB_LEAD, 256);
        const bool relp = rel && seg == 0;
#pragma unroll 1
        for (int n = seg ? Y_LEAD : 20 - YS - Y_LEAD; n > 0; n--) {
          wait_peeked(fb, ph);
          const uint32_t ad = ad0 + off, wd = ((SB + SLOT) >> 4) + DK + off;
          wgmma_fence();
          WgmmaSS<YN, 1, 0>::mma(ya, mkdesc64(ad), mkdesc(wd), accum);
          accum = true;
          WgmmaSS<YN, 1, 0>::mma(ya, mkdesc64(ad + 64), mkdesc(wd + 2), 1);
          wgmma_commit();
          wgmma_wait<1>();
          arrive_if(relp && eb != 0, eb);
          eb = fb + (rbars - bars) + (PEMPTY - PFULL);
          off += Y_STAGE >> 4; fb += 8;
          if (off == Y_STAGES * (Y_STAGE >> 4)) { off = 0; fb = bars + PFULL; ph ^= 1; }
          peek(fb, ph);
          WgmmaSS<YN, 1, 0>::mma(ya, mkdesc64(ad + 128), mkdesc(wd + 4), 1);
          WgmmaSS<YN, 1, 0>::mma(ya, mkdesc64(ad + 192), mkdesc(wd + 6), 1);
          wgmma_commit();
        }
      }
      if (wg == 0) bar_arrive(NB_LEAD, 256);
      wgmma_wait<0>();
      fence_regs(ya);
      uint4* sp = g_s + ((size_t)(m * 8 + slab) * 40 + (c0 >> 4)) * 32 + lane;
#pragma unroll
      for (int jj = 0; jj < YN / 16; jj++) {
        if (jj == 0)
          asm volatile("{\n.reg .pred p;\nsetp.eq.s32 p, %1, 0;\n@p red.relaxed.gpu.global.add.u32 [%0], 1;\n}" :: "l"(&g_flag[m * 32 + 28 + wg]), "r"(lane) : "memory");
        const uint32_t w0 = (pack_bf16(ya[8 * jj], ya[8 * jj + 1]) & ~1u) | par, w1 = pack_bf16(ya[8 * jj + 2], ya[8 * jj + 3]);
        const uint32_t w2 = (pack_bf16(ya[8 * jj + 4], ya[8 * jj + 5]) & ~1u) | par, w3 = pack_bf16(ya[8 * jj + 6], ya[8 * jj + 7]);
        asm volatile("st.relaxed.gpu.global.v2.u64 [%0], {%1, %2};" :: "l"(sp + jj * 32), "l"((uint64_t)w0 | ((uint64_t)w1 << 32)), "l"((uint64_t)w2 | ((uint64_t)w3 << 32)) : "memory");
      }
      };
      if (role == 2) y_job(IntTag<YN2>{}); else y_job(IntTag<YN0>{});
      asm volatile("barrier.cluster.arrive.relaxed.aligned;" ::: "memory");

    } else {
      float (&oa)[64] = acc[0];
      uint32_t xd[2][16];
      float sc0 = 0.f, sc1 = 0.f;
      uint32_t off = 0, fb = bars + PFULL, eb = 0, ph = 0;
      const uint32_t ad0 = (SB >> 4) + wg * 256 + DK;
      auto advance = [&]() {
        off += O_STAGE >> 4; fb += 8;
        if (off == O_STAGES * (O_STAGE >> 4)) { off = 0; fb = bars + PFULL; ph ^= 1; }
      };
      auto own_step = [&]() {
        wait_peeked(fb, ph);
        const uint32_t ad = ad0 + off, wd = ((SB + SLOT) >> 4) + DMN + off;
        advance();
        wgmma_fence();
        WgmmaSS<128, 0, 1>::mma(oa, mkdesc64(ad), mkdesc(wd), 1);
        peek(fb, ph);
        WgmmaSS<128, 0, 1>::mma(oa, mkdesc64(ad + 2), mkdesc(wd + 128), 1);
        WgmmaSS<128, 0, 1>::mma(oa, mkdesc64(ad + 512), mkdesc(wd + 256), 1);
        WgmmaSS<128, 0, 1>::mma(oa, mkdesc64(ad + 514), mkdesc(wd + 384), 1);
        wgmma_commit();
      };
      float4* hand = reinterpret_cast<float4*>(smem_raw + O_STAGES * O_STAGE) + (threadIdx.x & 127);
      {
        uint32_t dk[16];
#pragma unroll
        for (int jj = 0; jj < 16; jj++) dk[jj] = reinterpret_cast<const uint32_t*>(smem_raw + ONES_OFF)[jj * 4 + q];
        const int rho0 = (r8 & 1) + 4 * (slab & 1) + 8 * (4 * (slab >> 1) + (r8 >> 1));
        const float2 st[2] = {s_stat[rho0], s_stat[rho0 + 2]};
        sc0 = 0.25f * st[0].y * st[0].y; sc1 = 0.25f * st[1].y * st[1].y;
#pragma unroll
        for (int g = 0; g < 4; g++) {
          const int h = g >> 1, b8 = (g & 1) * 8;
          asm volatile("nanosleep.u32 %8;" : "+r"(xr[h][b8]), "+r"(xr[h][b8 + 1]), "+r"(xr[h][b8 + 2]), "+r"(xr[h][b8 + 3]),
                       "+r"(xr[h][b8 + 4]), "+r"(xr[h][b8 + 5]), "+r"(xr[h][b8 + 6]), "+r"(xr[h][b8 + 7]) : "n"(NAPX));
#pragma unroll
          for (int bit = 2; bit <= 4; bit <<= 1)
#pragma unroll
            for (int jj = b8; jj < b8 + 8; jj++)
              if (!(jj & bit)) {
                const uint32_t lo = xr[h][jj], hi = xr[h][jj | bit];
                xr[h][jj] = (r8 & bit) ? hi : lo; xr[h][jj | bit] = (r8 & bit) ? lo : hi;
              }
          const uint32_t mb = pack_bf16(st[h].x, st[h].x), rh = pack_bf16(st[h].y, st[h].y);
          const float rl_ = st[h].y - bf_lo(rh);
          const uint32_t rl = pack_bf16(rl_, rl_);
#pragma unroll
          for (int jj = b8; jj < b8 + 8; jj++) {
            const uint32_t d = hadd2_bf(xr[h][jj], mb);
            xd[h][jj] = hmul2_bf(hfma2_bf(d, rh, hmul2_bf(d, rl)), dk[jj]);
          }
        }
      }
      if (wg == 0) {
        const bool rel2 = (threadIdx.x & 127) < 2 * CLUSTER;
#pragma unroll 1
        for (int n = 0; n < O_SOLO; n++) {
          wait_peeked(fb, ph);
          const uint32_t ad = ad0 + off, wd = ((SB + SLOT) >> 4) + DMN + off;
          const uint32_t eb_next = fb + (rbars - bars) + (PEMPTY - PFULL);
          advance();
          wgmma_fence();
#pragma unroll
          for (int k = 0; k < 2; k++) {
            WgmmaSS<128, 0, 1>::mma(acc[0], mkdesc64(ad + k * 2), mkdesc(wd + k * 128), n != 0 || k);
            WgmmaSS<128, 0, 1>::mma(acc[1], mkdesc64(ad + 256 + k * 2), mkdesc(wd + k * 128), n != 0 || k);
          }
          wgmma_commit();
          wgmma_wait<1>();
          arrive_if(rel2 && eb != 0, eb);
          peek(fb, ph);
#pragma unroll
          for (int k = 0; k < 2; k++) {
            WgmmaSS<128, 0, 1>::mma(acc[0], mkdesc64(ad + 512 + k * 2), mkdesc(wd + 256 + k * 128), 1);
            WgmmaSS<128, 0, 1>::mma(acc[1], mkdesc64(ad + 768 + k * 2), mkdesc(wd + 256 + k * 128), 1);
          }
          wgmma_commit();
          eb = eb_next;
        }
        bar_arrive(NB_ORDER + 1, 256);
        wgmma_wait<0>();
        fence_regs(acc[0]); fence_regs(acc[1]);
        arrive_if(rel2, eb);
        eb = 0;
#pragma unroll
        for (int i = 0; i < 16; i++) hand[i * 128] = make_float4(acc[1][4 * i], acc[1][4 * i + 1], acc[1][4 * i + 2], acc[1][4 * i + 3]);
        bar_arrive(NB_HAND, 256);
      } else {
        off = (O_SOLO % O_STAGES) * (O_STAGE >> 4); fb += (O_SOLO % O_STAGES) * 8; ph = (O_SOLO / O_STAGES) & 1;
#pragma unroll
        for (int i = 0; i < 64; i++) oa[i] = 0.f;
      }
      float sa[64];
#pragma unroll
      for (int jj = 0; jj < 16; jj++) {
        sa[4 * jj] = bf_lo(xd[0][jj]); sa[4 * jj + 1] = bf_hi(xd[0][jj]); sa[4 * jj + 2] = bf_lo(xd[1][jj]); sa[4 * jj + 3] = bf_hi(xd[1][jj]);
      }
      fence_regs(sa);
      wgmma_fence();
      if (wg == 1) bar_sync(NB_ORDER + 1, 256);
#pragma unroll
      for (int t = 0; t < YS; t++) {
        wait_peeked(fb, ph);
        const uint32_t ad = (SB >> 4) + wg * 512 + DMN64 + off, wd = ((SB + SLOT) >> 4) + DK + off;
        const uint32_t eb_next = fb + (rbars - bars) + (PEMPTY - PFULL);
        advance();
        wgmma_fence();
#pragma unroll
        for (int k = 0; k < 4; k++) WgmmaSS<128, 1, 0>::mma(sa, mkdesc64(ad + k * 64), mkdesc(wd + k * 2), 1);
        peek(fb, ph);
        wgmma_commit();
        if (t) { wgmma_wait<1>(); arrive_if(rel, eb); }
        eb = eb_next;
      }
      {
        int n = 27 - O_LEAD - O_SOLO;
#pragma unroll 1
        do {
          const uint32_t eb_next = fb + (rbars - bars) + (PEMPTY - PFULL);
          own_step();
          wgmma_wait<1>();
          arrive_if(rel && (YS || eb != 0), eb);
          eb = eb_next;
        } while (--n);
      }
      wgmma_wait<0>();
      fence_regs(oa); fence_regs(sa);
      arrive_if(rel, eb);
      asm volatile("barrier.cluster.arrive.relaxed.aligned;" ::: "memory");
      if (wg == 1) {
        bar_sync(NB_HAND, 256);
#pragma unroll
        for (int i = 0; i < 16; i++) { const float4 v = hand[i * 128]; oa[4 * i] += v.x; oa[4 * i + 1] += v.y; oa[4 * i + 2] += v.z; oa[4 * i + 3] += v.w; }
        bar_sync(NB_LEAD, 256);
      }
      const uint4* sp = g_s + ((size_t)(m * 8 + slab) * 40 + (role - 3) * 8) * 32 + lane;
      uint64_t sw[16];
#pragma unroll
      for (int jj = 0; jj < 16; jj++) sw[jj] = par ^ 1u;
#pragma unroll
      for (int t = 0; t < O_LEAD; t++) {
        own_step();
        if (t == S_AT) {
          const uint32_t there = lds_volatile(bars + READY) & (0x10000000u << wg);
#pragma unroll
          for (int jj = 0; jj < 8; jj++)
            asm volatile("{\n.reg .pred p;\nsetp.ne.u32 p, %3, 0;\n@p ld.relaxed.gpu.global.v2.u64 {%0, %1}, [%2];\n}" : "+l"(sw[2 * jj]), "+l"(sw[2 * jj + 1]) : "l"(sp + jj * 32), "r"(there) : "memory");
        }
      }
      if (wg == 0) bar_arrive(NB_LEAD, 256);
      smem_wait_bits(bars + READY, 0x10000000u << wg);
      {
        const uint32_t t0 = clock32();
        while (true) {
          uint32_t st[8], bad = 0;
#pragma unroll
          for (int jj = 0; jj < 8; jj++) {
            asm("lop3.b32 %0, %1, %2, %3, 0x7e;" : "=r"(st[jj]) : "r"(par), "r"((uint32_t)sw[2 * jj]), "r"((uint32_t)sw[2 * jj + 1]));
            asm("or.b32 %0, %0, %1;" : "+r"(bad) : "r"(st[jj]));
          }
          if (!__any_sync(0xffffffffu, bad & 1u) || clock32() - t0 > 1000000000u) break;
#pragma unroll
          for (int jj = 0; jj < 8; jj++)
            if (st[jj] & 1u) asm volatile("ld.relaxed.gpu.global.v2.u64 {%0, %1}, [%2];" : "=l"(sw[2 * jj]), "=l"(sw[2 * jj + 1]) : "l"(sp + jj * 32) : "memory");
        }
      }
#pragma unroll
      for (int jj = 0; jj < 16; jj++) {
        const uint32_t lo = (uint32_t)sw[jj] ^ par, hi = (uint32_t)(sw[jj] >> 32);
        sa[4 * jj] += bf_lo(lo); sa[4 * jj + 1] += bf_hi(lo); sa[4 * jj + 2] += bf_lo(hi); sa[4 * jj + 3] += bf_hi(hi);
      }
      fence_regs(sa);
      constexpr int T0 = 27 + YS - O_STAGES;
      if (wg == 0) mbar_wait(bars + PEMPTY + (T0 % O_STAGES) * 8, (T0 / O_STAGES + 1) & 1);
      uint8_t* buf = smem_raw + (wg ? O_STAGES : T0 % O_STAGES) * O_STAGE + w4 * 8192;
      wgmma_wait<0>();
      fence_regs(oa);
#pragma unroll
      for (int t = 0; t < 4; t++) {
#pragma unroll
        for (int j4 = 0; j4 < 4; j4++) {
          const int jj = t * 4 + j4;
          float r[4];
#pragma unroll
          for (int i = 0; i < 4; i++) {
            const float h = oa[4 * jj + i] * ((i & 2) ? sc1 : sc0);
            const uint32_t xw = xr[i >> 1][jj];
            r[i] = fmaf(sa[4 * jj + i], fmaf(h, tanh_fast(h), h), (i & 1) ? bf_hi(xw) : bf_lo(xw));
          }
          uint8_t* p = buf + t * 2048 + r8 * 128 + (((j4 * 2 + (q >> 1)) ^ r8) << 4) + (q & 1) * 8;
          *reinterpret_cast<float2*>(p) = make_float2(r[0], r[1]);
          *reinterpret_cast<float2*>(p + 1024) = make_float2(r[2], r[3]);
        }
        asm volatile("fence.proxy.async.shared::cta;" ::: "memory");
        __syncwarp();
        if (elect_one()) {
          asm volatile("cp.async.bulk.tensor.5d.global.shared::cta.bulk_group [%0, {%2, %2, %3, %4, %5}], [%1];"
            :: "l"(&maps.out), "r"(smem_u32(buf) + t * 2048), "r"(0), "r"(m * 4 + (slab & 1) * 2), "r"(slab >> 1), "r"((role - 3) * 4 + t) : "memory");
        }
      }
      asm volatile("cp.async.bulk.commit_group;" ::: "memory");
      asm volatile("cp.async.bulk.wait_group.read 0;" ::: "memory");
      __syncwarp();
    }
    asm volatile("barrier.cluster.wait.aligned;" ::: "memory");
  }
}

__device__ __forceinline__ float f_ld(const __nv_bfloat16* p, size_t i) { return __bfloat162float(p[i]); }
__global__ void fb_ln(const __nv_bfloat16* x) {
  const int row = blockIdx.x * 8 + (threadIdx.x >> 5), lane = threadIdx.x & 31;
  float s = 0.f, v = 0.f;
  for (int i = lane; i < D_; i += 32) s += f_ld(x, (size_t)row * D_ + i);
  for (int o = 16; o; o >>= 1) s += __shfl_xor_sync(0xffffffffu, s, o);
  const float mean = s / D_;
  for (int i = lane; i < D_; i += 32) { const float d = f_ld(x, (size_t)row * D_ + i) - mean; v += d * d; }
  for (int o = 16; o; o >>= 1) v += __shfl_xor_sync(0xffffffffu, v, o);
  const float mb = round_bf(mean), den = round_bf(sqrtf(round_bf(round_bf(v / D_) + 1e-5f)));
  __nv_bfloat16* xn = reinterpret_cast<__nv_bfloat16*>(g_s);
  for (int i = lane; i < D_; i += 32) xn[(size_t)row * D_ + i] = __float2bfloat16_rn(round_bf(f_ld(x, (size_t)row * D_ + i) - mb) / den);
}
__global__ void fb_in(const __nv_bfloat16* bre, const __nv_bfloat16* bim, const __nv_bfloat16* wg, const __nv_bfloat16* wu, float* out) {
  const int n = blockIdx.x * 64 + threadIdx.x, t = blockIdx.y;
  const __nv_bfloat16* xn = reinterpret_cast<const __nv_bfloat16*>(g_s) + (size_t)t * D_;
  float a = 0.f, b = 0.f;
  if (n < P_) {
    for (int k = 0; k < D_; k++) { const float v = f_ld(xn, k); a += v * f_ld(bre, (size_t)n * D_ + k); b += v * f_ld(bim, (size_t)n * D_ + k); }
    out[(size_t)t * P_ + n] = a; reinterpret_cast<float*>(g_hT)[(size_t)t * P_ + n] = b;
  } else {
    const int f = n - P_;
    for (int k = 0; k < D_; k++) { const float v = f_ld(xn, k); a += v * f_ld(wg, (size_t)k * F_ + f); b += v * f_ld(wu, (size_t)k * F_ + f); }
    a = round_bf(a);
    const float g = round_bf(0.5f * a * (1.0f + tanhf(0.7978845608028654f * (a + 0.044715f * a * a * a))));
    reinterpret_cast<__nv_bfloat16*>(g_H)[(size_t)t * F_ + f] = __float2bfloat16_rn(g * round_bf(b));
  }
}
__global__ void fb_scan(const __nv_bfloat16* lre, const __nv_bfloat16* lim, const __nv_bfloat16* ldt, float* out) {
  float* him = reinterpret_cast<float*>(g_hT);
  const int p = blockIdx.x * 64 + threadIdx.x;
  cplx lam, cf, h = {0.f, 0.f};
  ssm_params(f_ld(lre, p), f_ld(lim, p), f_ld(ldt, p), lam, cf);
  for (int t = 0; t < L_; t++) {
    h = cfma(lam, h, cmul(cf, cplx{out[(size_t)t * P_ + p], him[(size_t)t * P_ + p]}));
    out[(size_t)t * P_ + p] = h.r; him[(size_t)t * P_ + p] = h.i;
  }
}
__global__ void fb_out(const __nv_bfloat16* x, const __nv_bfloat16* cre, const __nv_bfloat16* cim, const __nv_bfloat16* dsk,
                       const __nv_bfloat16* wd, float* out) {
  const int d = threadIdx.x, t = blockIdx.x;
  const float* him = reinterpret_cast<const float*>(g_hT);
  float y = 0.f, o = 0.f;
  for (int p = 0; p < P_; p++) y += out[(size_t)t * P_ + p] * f_ld(cre, (size_t)d * P_ + p) - him[(size_t)t * P_ + p] * f_ld(cim, (size_t)d * P_ + p);
  const __nv_bfloat16* H = reinterpret_cast<const __nv_bfloat16*>(g_H) + (size_t)t * F_;
  for (int f = 0; f < F_; f++) o += f_ld(H, f) * f_ld(wd, (size_t)f * D_ + d);
  y += round_bf(f_ld(reinterpret_cast<const __nv_bfloat16*>(g_s), (size_t)t * D_ + d) * f_ld(dsk, d));
  o = round_bf(o);
  __syncthreads();
  out[(size_t)t * D_ + d] = f_ld(x, (size_t)t * D_ + d) + y * round_bf(o / (1.0f + expf(-o)));
}

typedef CUresult (*EncodeFn)(CUtensorMap*, CUtensorMapDataType, cuuint32_t, void*, const cuuint64_t*, const cuuint64_t*,
                             const cuuint32_t*, const cuuint32_t*, CUtensorMapInterleave, CUtensorMapSwizzle,
                             CUtensorMapL2promotion, CUtensorMapFloatOOBfill);

bool encode(EncodeFn fn, CUtensorMap* m, const void* base, int rank, const uint64_t* dims, const uint64_t* strides, const uint32_t* box,
            CUtensorMapDataType dt = CU_TENSOR_MAP_DATA_TYPE_BFLOAT16) {
  cuuint64_t d[5], s[5]; cuuint32_t b[5], e[5];
  for (int i = 0; i < rank; i++) { d[i] = dims[i]; b[i] = box[i]; e[i] = 1; if (i + 1 < rank) s[i] = strides[i]; }
  CUresult r = fn(m, dt, rank, const_cast<void*>(base), d, s, b, e, CU_TENSOR_MAP_INTERLEAVE_NONE,
                  CU_TENSOR_MAP_SWIZZLE_128B, CU_TENSOR_MAP_L2_PROMOTION_L2_256B, CU_TENSOR_MAP_FLOAT_OOB_FILL_NONE);
  if (r != CUDA_SUCCESS) { fprintf(stderr, "cuTensorMapEncodeTiled failed: %d\n", (int)r); return false; }
  return true;
}
bool encode2d(EncodeFn fn, CUtensorMap* m, const void* base, uint64_t inner, uint64_t outer, uint32_t box_outer) {
  const uint64_t dims[2] = {inner, outer}, str[1] = {inner * 2};
  const uint32_t box[2] = {64, box_outer};
  return encode(fn, m, base, 2, dims, str, box);
}

}

extern "C" void kernel_launch(void* const* d_in, const int* in_sizes, int n_in, void* d_out, int out_size) {
  (void)in_sizes; (void)n_in; (void)out_size;
  typedef const __nv_bfloat16* BP;
  cudaLaunchConfig_t cfg = {};
  cfg.gridDim = dim3(NCTA); cfg.blockDim = dim3(384); cfg.dynamicSmemBytes = SMEM_BYTES; cfg.stream = cudaStreamPerThread;
  cudaLaunchAttribute at[1];
  at[0].id = cudaLaunchAttributeClusterDimension; at[0].val.clusterDim.y = 1; at[0].val.clusterDim.z = 1;
  cfg.attrs = at; cfg.numAttrs = 1;
  static EncodeFn fn = nullptr;
  static int resident = -1, small_gpc = 0;
  if (resident < 0) {
    void* p = nullptr; cudaDriverEntryPointQueryResult st;
    if (cudaGetDriverEntryPoint("cuTensorMapEncodeTiled", &p, cudaEnableDefault, &st) == cudaSuccess) fn = (EncodeFn)p;
    cudaFuncSetAttribute(fused_kernel, cudaFuncAttributeMaxDynamicSharedMemorySize, SMEM_BYTES);
    int n[3] = {0, 0, 0};
    for (int i = 0; i < 3; i++) {
      at[0].val.clusterDim.x = 2 + 2 * i;
      if (cudaOccupancyMaxActiveClusters(&n[i], fused_kernel, &cfg) != cudaSuccess) { n[i] = 0; (void)cudaGetLastError(); }
    }
    resident = fn && n[0] >= NCTA / 2;
    small_gpc = n[0] == 66 && n[1] == 30 && n[2] == 17;
  }
  if (!resident) {
    fb_ln<<<L_ / 8, 256, 0, cudaStreamPerThread>>>((BP)d_in[0]);
    fb_in<<<dim3((P_ + F_) / 64, L_), 64, 0, cudaStreamPerThread>>>((BP)d_in[3], (BP)d_in[4], (BP)d_in[10], (BP)d_in[11], (float*)d_out);
    fb_scan<<<P_ / 64, 64, 0, cudaStreamPerThread>>>((BP)d_in[1], (BP)d_in[2], (BP)d_in[7], (float*)d_out);
    fb_out<<<L_, D_, 0, cudaStreamPerThread>>>((BP)d_in[0], (BP)d_in[5], (BP)d_in[6], (BP)d_in[8], (BP)d_in[12], (float*)d_out);
    return;
  }
  at[0].val.clusterDim.x = 2;
  Maps maps;
  bool ok = true;
  {
    const uint64_t dims[4] = {D_, 2, L_ / 32, 16}, str[3] = {D_ * 2, 32 * D_ * 2, 2 * D_ * 2};
    const uint32_t box[4] = {64, 2, 4, 16};
    ok &= encode(fn, &maps.x, d_in[0], 4, dims, str, box);
  }
  ok &= encode2d(fn, &maps.bre, d_in[3], D_, P_, 64);
  ok &= encode2d(fn, &maps.bim, d_in[4], D_, P_, 64);
  ok &= encode2d(fn, &maps.wg, d_in[10], F_, D_, 64);
  ok &= encode2d(fn, &maps.wu, d_in[11], F_, D_, 64);
  {
    const uint64_t dims[5] = {D_, 2, 4, 4, F_ / 32}, str[4] = {D_ * 2, 8 * D_ * 2, 2 * D_ * 2, 32 * D_ * 2};
    const uint32_t box[5] = {64, 2, 4, 4, 2};
    ok &= encode(fn, &maps.wd, d_in[12], 5, dims, str, box);
  }
  ok &= encode2d(fn, &maps.cre0, d_in[5], P_, D_, 112);
  ok &= encode2d(fn, &maps.cre1, d_in[5], P_, D_, 104);
  ok &= encode2d(fn, &maps.cim0, d_in[6], P_, D_, 112);
  ok &= encode2d(fn, &maps.cim1, d_in[6], P_, D_, 104);
  ok &= encode2d(fn, &maps.cre2, d_in[5], P_, D_, 64);
  ok &= encode2d(fn, &maps.cim2, d_in[6], P_, D_, 64);
  {
    const uint64_t dims[5] = {32, 8, L_ / 32, 4, D_ / 32}, str[4] = {D_ * 4, 32 * D_ * 4, 8 * D_ * 4, 128};
    const uint32_t box[5] = {32, 8, 2, 1, 1};
    ok &= encode(fn, &maps.out, d_out, 5, dims, str, box, CU_TENSOR_MAP_DATA_TYPE_FLOAT32);
  }
  if (!ok) return;

  Ptrs ptrs = {(BP)d_in[0], (BP)d_in[1], (BP)d_in[2], (BP)d_in[7], (BP)d_in[8], (BP)d_in[3], (BP)d_in[4], (BP)d_in[5], (BP)d_in[6], (BP)d_in[12], 0, {0}};
  for (int c = 0; c < NCTA / 2; c++) {
    int mp, row;
    if (c < 2) { ptrs.work[c * 2] = 128 + c * 2; ptrs.work[c * 2 + 1] = 129 + c * 2; continue; }
    if (small_gpc) {
      if (c < 4) { mp = 1; row = c + 2; }
      else if (c < 36) { mp = (c - 4) & 7; row = (c - 4) >> 3; }
      else if (c < 64) { const int i = c - 36, r7 = i / 7, p7 = i - r7 * 7; mp = p7 ? p7 + 1 : 0; row = 4 + r7; }
      else { mp = 1; row = c - 58; }
    } else {
      mp = (c + 4) & 7; row = ((c + 60) >> 3) & 7;
    }
    for (int r = 0; r < 2; r++) ptrs.work[c * 2 + r] = (uint32_t)((((row + 3) & 7) << 4) | (mp * 2 + r));
  }
  cudaLaunchKernelEx(&cfg, fused_kernel, maps, ptrs);
}
```
